```python
import torch

def _softmax(x, axis=-1):
    return torch.softmax(x, dim=axis)
def _gelu(x):
    return torch.nn.functional.gelu(x, approximate="tanh")
def _silu(x):
    return torch.nn.functional.silu(x)
def _sigmoid(x):
    return torch.sigmoid(x)
def _layernorm(x, axis=-1, eps=1e-5):
    m = x.mean(dim=axis, keepdim=True)
    v = x.var(dim=axis, keepdim=True, unbiased=False)
    return (x - m) / torch.sqrt(v + eps)
def _scatter_add(tgt, idx, src, axis=0):
    return tgt.clone().index_add_(axis, idx, src)
def _segment_sum(src, seg, n):
    out = torch.zeros((n,) + src.shape[1:], dtype=src.dtype)
    return out.index_add_(0, seg, src)
def _pad(x, pw):
    flat = tuple(v for pair in reversed(pw) for v in pair)
    return torch.nn.functional.pad(x, flat)

kernel_name = 'gated_mix__ssm_conv_h3__ssm_conv_s4d__prompt'

def setup_inputs():

    _w = (lambda a: (lambda t: t.to(torch.bfloat16) if t.is_floating_point() else t)(torch.as_tensor(a)))
    def _A_setup():
        B, S, D = 1, 2048, 576
        ks = 4
        return {
            "q": _w((lambda *s: torch.randn(*s, dtype=torch.bfloat16) * 0.05)(B, S, D)),
            "k": _w((lambda *s: torch.randn(*s, dtype=torch.bfloat16) * 0.8)(B, S, D)),
            "v": _w((lambda *s: torch.randn(*s, dtype=torch.bfloat16) * 0.8)(B, S, D)),
            "shift_k": _w((lambda *s: torch.randn(*s, dtype=torch.bfloat16) * 0.8)(D, ks) * 0.5),
            "ssm_k": _w((lambda *s: torch.randn(*s, dtype=torch.bfloat16) * 0.8)(D, S) * (1.0 / S ** 0.5)),
            "ssm_D": _w((lambda *s: torch.randn(*s, dtype=torch.bfloat16) * 0.8)(D)),
        }
    _A_in = _A_setup()

    def _B_setup():
        Bsz, L, D, N = 1, 2048, 576, 128
        return {
            "u": _w((lambda *s: torch.randn(*s, dtype=torch.bfloat16) * 0.05)(Bsz, L, D)),
            "log_A_real": _w((lambda *s: torch.randn(*s, dtype=torch.bfloat16) * 3.2)(D, N) * 0.5),
            "A_imag": _w((lambda *s: torch.randn(*s, dtype=torch.bfloat16) * 0.2)(D, N) * 3.14),
            "C_real": _w((lambda *s: torch.randn(*s, dtype=torch.bfloat16) * 3.2)(D, N) / N ** 0.5),
            "C_imag": _w((lambda *s: torch.randn(*s, dtype=torch.bfloat16) * 3.2)(D, N) / N ** 0.5),
            "log_dt": _w((lambda *s: torch.randn(*s, dtype=torch.bfloat16) * 0.2)(D) * 0.5 - 4.0),
            "D_skip": _w((lambda *s: torch.randn(*s, dtype=torch.bfloat16) * 0.4)(D)),
        }
    _B_in = _B_setup()

    return {
        "A_q": _A_in["q"],
        "A_k": _A_in["k"],
        "A_v": _A_in["v"],
        "A_shift_k": _A_in["shift_k"],
        "A_ssm_k": _A_in["ssm_k"],
        "A_ssm_D": _A_in["ssm_D"],
        "B_u": _B_in["u"],
        "B_log_A_real": _B_in["log_A_real"],
        "B_A_imag": _B_in["A_imag"],
        "B_C_real": _B_in["C_real"],
        "B_C_imag": _B_in["C_imag"],
        "B_log_dt": _B_in["log_dt"],
        "B_D_skip": _B_in["D_skip"],
        "gate_w": _w((lambda *s: torch.randn(*s, dtype=torch.bfloat16) * 0.05)(576) * 16.0),
    }

def reference(A_q, A_k, A_v, A_shift_k, A_ssm_k, A_ssm_D, B_u, B_log_A_real, B_A_imag, B_C_real, B_C_imag, B_log_dt, B_D_skip, gate_w):
    def _A_ref(q, k, v, shift_k, ssm_k, ssm_D):
        B, S, D = q.shape
        ks = shift_k.shape[-1]
        k_pad = _pad(k, ((0, 0), (ks - 1, 0), (0, 0)))
        k_shift = torch.zeros_like(k)
        for t in range(ks):
            k_shift = k_shift + k_pad[:, t:t + S, :] * shift_k[:, ks - 1 - t][None, None, :]
        kv = k_shift * v
        L = 2 * S
        kv_pad = _pad(kv, ((0, 0), (0, S), (0, 0)))
        kf_pad = _pad(ssm_k, ((0, 0), (0, S)))
        kv_f = (lambda x, axes=(-2,-1): torch.fft.rfft2(x.float(), dim=axes))(kv_pad[:, None, :, :], axes=(1, 2))
        kf_f = (lambda x, axes=(-2,-1): torch.fft.rfft2(x.float(), dim=axes))(kf_pad[:, None, :], axes=(1, 2))
        kf_f = (lambda x, *d: x.permute(*d))(kf_f, 1, 2, 0)
        y_f = kv_f * kf_f[None, :, :, :]
        y = (lambda x, s, axes=(-2,-1): torch.fft.irfft2(x, s=s, dim=axes).to(torch.bfloat16))(y_f, (1, L), axes=(1, 2))[:, 0, :S, :]
        y = y + kv * ssm_D[None, None, :]
        return q * y

    def _B_ref(u, log_A_real, A_imag, C_real, C_imag, log_dt, D_skip):
        L = u.shape[1]
        dt = torch.exp(log_dt)
        A = -torch.exp(log_A_real) + 1j * A_imag
        C = (C_real + 1j * C_imag) * dt[:, None]
        pos = (lambda x, dt: x.to(dt))(torch.arange(L), log_dt.dtype)
        P = torch.exp((A * dt[:, None])[:, :, None] * pos[None, None, :])
        K = 2.0 * torch.einsum("dn,dnl->dl", C, P).real
        L2 = 2 * L
        u_t = (lambda x, *d: x.permute(*d))(u, 0, 2, 1)
        Kf = (lambda x, *a, **k: torch.fft.rfft(x.float(), *a, **k))(K, L2)
        Uf = (lambda x, *a, **k: torch.fft.rfft(x.float(), *a, **k))(u_t, L2)
        y = (lambda x, *a, **k: torch.fft.irfft(x, *a, **k).to(torch.bfloat16))(Uf * Kf[None, :, :], L2)[:, :, :L]
        y = (lambda x, *d: x.permute(*d))(y, 0, 2, 1)
        return y + u * D_skip[None, None, :]

    x = A_q
    g = _sigmoid((x * gate_w).sum(-1, keepdims=True))
    a = _A_ref(x, A_k, A_v, A_shift_k, A_ssm_k, A_ssm_D)
    b = _B_ref(x, B_log_A_real, B_A_imag, B_C_real, B_C_imag, B_log_dt, B_D_skip)
    return g * a + (1 - g) * b
```

```cpp
#include <cuda_runtime.h>
#include <cuda_bf16.h>
#include <cuda_fp16.h>
#include <cuda.h>
#include <stdint.h>

typedef __nv_bfloat16 bf16;
#define KVMODE 1
#define STAGGER 1
#define WAITMODE 1

constexpr int S_LEN = 2048, D_CH = 576, NST = 128;
constexpr int NCL = 15, CLS = 8, RMAX = 5;
constexpr int PITCH = RMAX * 16;

constexpr int TAB_SZ = 8320;
constexpr int TAB = 0;
constexpr int RAWQ = TAB + 5 * TAB_SZ;
constexpr int RAWV = RAWQ + 256 * PITCH;
constexpr int RAWK = TAB + 10 * TAB_SZ;
constexpr int SCR = RAWK + 288 * PITCH;
constexpr int SCR_SZ = 32768;
constexpr int UB = SCR + 2 * SCR_SZ;
constexpr int UB_SZ = 4112;
constexpr int PAR = UB + 10 * UB_SZ;
constexpr int PAR_SZ = 1040;
constexpr int GBUF = PAR + RMAX * PAR_SZ;
constexpr int BARS = GBUF + 4096;
constexpr int PAR2 = BARS + 256;
constexpr int PAR3 = PAR2 + 448;
constexpr int PROFB = PAR2 + 512;
constexpr int SMEM_TOTAL = PROFB + 384;
constexpr int RECV = RAWK;
constexpr int RECV_SZ = 4224, RECV_PITCH = 528;
constexpr int PLANE = 4096 + 128;
constexpr int OUTB = SCR + 17408;
constexpr int CMP_H = 1312;
constexpr int CMP = 28672;
static_assert(SMEM_TOTAL <= 232448 && RAWQ % 128 == 0 && RAWK % 128 == 0 && RAWV + 256 * PITCH <= RAWK, "smem");
static_assert(RMAX * RECV_SZ <= 288 * PITCH && OUTB % 256 == 0, "smem");
enum { B_Q = 0, B_KV = 4, B_U = 5, B_KVT = 10, B_G = 11, B_O = 12, B_END = 17 };
enum { NB_WG = 1, NB_AUX = 3, NB_TURN = 4, NB_TAB = 6 };

__device__ unsigned int g_gate_part[NCL * S_LEN];
__device__ unsigned int g_epoch[NCL * CLS];
#define TS(e)
#define TG(e)
#define TS_DUMP()

template<int N> __device__ __forceinline__ void wg_rs(float (&d)[128], uint32_t a0, uint32_t a1, uint32_t a2, uint32_t a3, uint64_t desc, int sc);
template<> __device__ __forceinline__ void wg_rs<16>(float (&d)[128], uint32_t a0, uint32_t a1, uint32_t a2, uint32_t a3, uint64_t desc, int sc) {
  asm volatile("{\n.reg .pred p;\nsetp.ne.b32 p, %13, 0;\n"
  "wgmma.mma_async.sync.aligned.m64n16k16.f32.bf16.bf16 {%0,%1,%2,%3,%4,%5,%6,%7}, {%8,%9,%10,%11}, %12, p, 1, 1, 0;\n}\n"
  : "+f"(d[0]),"+f"(d[1]),"+f"(d[2]),"+f"(d[3]),"+f"(d[4]),"+f"(d[5]),"+f"(d[6]),"+f"(d[7])
  : "r"(a0), "r"(a1), "r"(a2), "r"(a3), "l"(desc), "r"(sc));
}
template<> __device__ __forceinline__ void wg_rs<32>(float (&d)[128], uint32_t a0, uint32_t a1, uint32_t a2, uint32_t a3, uint64_t desc, int sc) {
  asm volatile("{\n.reg .pred p;\nsetp.ne.b32 p, %21, 0;\n"
  "wgmma.mma_async.sync.aligned.m64n32k16.f32.bf16.bf16 {%0,%1,%2,%3,%4,%5,%6,%7,%8,%9,%10,%11,%12,%13,%14,%15}, {%16,%17,%18,%19}, %20, p, 1, 1, 0;\n}\n"
  : "+f"(d[0]),"+f"(d[1]),"+f"(d[2]),"+f"(d[3]),"+f"(d[4]),"+f"(d[5]),"+f"(d[6]),"+f"(d[7]),"+f"(d[8]),"+f"(d[9]),"+f"(d[10]),"+f"(d[11]),"+f"(d[12]),"+f"(d[13]),"+f"(d[14]),"+f"(d[15])
  : "r"(a0), "r"(a1), "r"(a2), "r"(a3), "l"(desc), "r"(sc));
}
template<> __device__ __forceinline__ void wg_rs<48>(float (&d)[128], uint32_t a0, uint32_t a1, uint32_t a2, uint32_t a3, uint64_t desc, int sc) {
  asm volatile("{\n.reg .pred p;\nsetp.ne.b32 p, %29, 0;\n"
  "wgmma.mma_async.sync.aligned.m64n48k16.f32.bf16.bf16 {%0,%1,%2,%3,%4,%5,%6,%7,%8,%9,%10,%11,%12,%13,%14,%15,%16,%17,%18,%19,%20,%21,%22,%23}, {%24,%25,%26,%27}, %28, p, 1, 1, 0;\n}\n"
  : "+f"(d[0]),"+f"(d[1]),"+f"(d[2]),"+f"(d[3]),"+f"(d[4]),"+f"(d[5]),"+f"(d[6]),"+f"(d[7]),"+f"(d[8]),"+f"(d[9]),"+f"(d[10]),"+f"(d[11]),"+f"(d[12]),"+f"(d[13]),"+f"(d[14]),"+f"(d[15]),"+f"(d[16]),"+f"(d[17]),"+f"(d[18]),"+f"(d[19]),"+f"(d[20]),"+f"(d[21]),"+f"(d[22]),"+f"(d[23])
  : "r"(a0), "r"(a1), "r"(a2), "r"(a3), "l"(desc), "r"(sc));
}
template<> __device__ __forceinline__ void wg_rs<64>(float (&d)[128], uint32_t a0, uint32_t a1, uint32_t a2, uint32_t a3, uint64_t desc, int sc) {
  asm volatile("{\n.reg .pred p;\nsetp.ne.b32 p, %37, 0;\n"
  "wgmma.mma_async.sync.aligned.m64n64k16.f32.bf16.bf16 {%0,%1,%2,%3,%4,%5,%6,%7,%8,%9,%10,%11,%12,%13,%14,%15,%16,%17,%18,%19,%20,%21,%22,%23,%24,%25,%26,%27,%28,%29,%30,%31}, {%32,%33,%34,%35}, %36, p, 1, 1, 0;\n}\n"
  : "+f"(d[0]),"+f"(d[1]),"+f"(d[2]),"+f"(d[3]),"+f"(d[4]),"+f"(d[5]),"+f"(d[6]),"+f"(d[7]),"+f"(d[8]),"+f"(d[9]),"+f"(d[10]),"+f"(d[11]),"+f"(d[12]),"+f"(d[13]),"+f"(d[14]),"+f"(d[15]),"+f"(d[16]),"+f"(d[17]),"+f"(d[18]),"+f"(d[19]),"+f"(d[20]),"+f"(d[21]),"+f"(d[22]),"+f"(d[23]),"+f"(d[24]),"+f"(d[25]),"+f"(d[26]),"+f"(d[27]),"+f"(d[28]),"+f"(d[29]),"+f"(d[30]),"+f"(d[31])
  : "r"(a0), "r"(a1), "r"(a2), "r"(a3), "l"(desc), "r"(sc));
}
template<> __device__ __forceinline__ void wg_rs<80>(float (&d)[128], uint32_t a0, uint32_t a1, uint32_t a2, uint32_t a3, uint64_t desc, int sc) {
  asm volatile("{\n.reg .pred p;\nsetp.ne.b32 p, %45, 0;\n"
  "wgmma.mma_async.sync.aligned.m64n80k16.f32.bf16.bf16 {%0,%1,%2,%3,%4,%5,%6,%7,%8,%9,%10,%11,%12,%13,%14,%15,%16,%17,%18,%19,%20,%21,%22,%23,%24,%25,%26,%27,%28,%29,%30,%31,%32,%33,%34,%35,%36,%37,%38,%39}, {%40,%41,%42,%43}, %44, p, 1, 1, 0;\n}\n"
  : "+f"(d[0]),"+f"(d[1]),"+f"(d[2]),"+f"(d[3]),"+f"(d[4]),"+f"(d[5]),"+f"(d[6]),"+f"(d[7]),"+f"(d[8]),"+f"(d[9]),"+f"(d[10]),"+f"(d[11]),"+f"(d[12]),"+f"(d[13]),"+f"(d[14]),"+f"(d[15]),"+f"(d[16]),"+f"(d[17]),"+f"(d[18]),"+f"(d[19]),"+f"(d[20]),"+f"(d[21]),"+f"(d[22]),"+f"(d[23]),"+f"(d[24]),"+f"(d[25]),"+f"(d[26]),"+f"(d[27]),"+f"(d[28]),"+f"(d[29]),"+f"(d[30]),"+f"(d[31]),"+f"(d[32]),"+f"(d[33]),"+f"(d[34]),"+f"(d[35]),"+f"(d[36]),"+f"(d[37]),"+f"(d[38]),"+f"(d[39])
  : "r"(a0), "r"(a1), "r"(a2), "r"(a3), "l"(desc), "r"(sc));
}
template<> __device__ __forceinline__ void wg_rs<96>(float (&d)[128], uint32_t a0, uint32_t a1, uint32_t a2, uint32_t a3, uint64_t desc, int sc) {
  asm volatile("{\n.reg .pred p;\nsetp.ne.b32 p, %53, 0;\n"
  "wgmma.mma_async.sync.aligned.m64n96k16.f32.bf16.bf16 {%0,%1,%2,%3,%4,%5,%6,%7,%8,%9,%10,%11,%12,%13,%14,%15,%16,%17,%18,%19,%20,%21,%22,%23,%24,%25,%26,%27,%28,%29,%30,%31,%32,%33,%34,%35,%36,%37,%38,%39,%40,%41,%42,%43,%44,%45,%46,%47}, {%48,%49,%50,%51}, %52, p, 1, 1, 0;\n}\n"
  : "+f"(d[0]),"+f"(d[1]),"+f"(d[2]),"+f"(d[3]),"+f"(d[4]),"+f"(d[5]),"+f"(d[6]),"+f"(d[7]),"+f"(d[8]),"+f"(d[9]),"+f"(d[10]),"+f"(d[11]),"+f"(d[12]),"+f"(d[13]),"+f"(d[14]),"+f"(d[15]),"+f"(d[16]),"+f"(d[17]),"+f"(d[18]),"+f"(d[19]),"+f"(d[20]),"+f"(d[21]),"+f"(d[22]),"+f"(d[23]),"+f"(d[24]),"+f"(d[25]),"+f"(d[26]),"+f"(d[27]),"+f"(d[28]),"+f"(d[29]),"+f"(d[30]),"+f"(d[31]),"+f"(d[32]),"+f"(d[33]),"+f"(d[34]),"+f"(d[35]),"+f"(d[36]),"+f"(d[37]),"+f"(d[38]),"+f"(d[39]),"+f"(d[40]),"+f"(d[41]),"+f"(d[42]),"+f"(d[43]),"+f"(d[44]),"+f"(d[45]),"+f"(d[46]),"+f"(d[47])
  : "r"(a0), "r"(a1), "r"(a2), "r"(a3), "l"(desc), "r"(sc));
}
template<> __device__ __forceinline__ void wg_rs<112>(float (&d)[128], uint32_t a0, uint32_t a1, uint32_t a2, uint32_t a3, uint64_t desc, int sc) {
  asm volatile("{\n.reg .pred p;\nsetp.ne.b32 p, %61, 0;\n"
  "wgmma.mma_async.sync.aligned.m64n112k16.f32.bf16.bf16 {%0,%1,%2,%3,%4,%5,%6,%7,%8,%9,%10,%11,%12,%13,%14,%15,%16,%17,%18,%19,%20,%21,%22,%23,%24,%25,%26,%27,%28,%29,%30,%31,%32,%33,%34,%35,%36,%37,%38,%39,%40,%41,%42,%43,%44,%45,%46,%47,%48,%49,%50,%51,%52,%53,%54,%55}, {%56,%57,%58,%59}, %60, p, 1, 1, 0;\n}\n"
  : "+f"(d[0]),"+f"(d[1]),"+f"(d[2]),"+f"(d[3]),"+f"(d[4]),"+f"(d[5]),"+f"(d[6]),"+f"(d[7]),"+f"(d[8]),"+f"(d[9]),"+f"(d[10]),"+f"(d[11]),"+f"(d[12]),"+f"(d[13]),"+f"(d[14]),"+f"(d[15]),"+f"(d[16]),"+f"(d[17]),"+f"(d[18]),"+f"(d[19]),"+f"(d[20]),"+f"(d[21]),"+f"(d[22]),"+f"(d[23]),"+f"(d[24]),"+f"(d[25]),"+f"(d[26]),"+f"(d[27]),"+f"(d[28]),"+f"(d[29]),"+f"(d[30]),"+f"(d[31]),"+f"(d[32]),"+f"(d[33]),"+f"(d[34]),"+f"(d[35]),"+f"(d[36]),"+f"(d[37]),"+f"(d[38]),"+f"(d[39]),"+f"(d[40]),"+f"(d[41]),"+f"(d[42]),"+f"(d[43]),"+f"(d[44]),"+f"(d[45]),"+f"(d[46]),"+f"(d[47]),"+f"(d[48]),"+f"(d[49]),"+f"(d[50]),"+f"(d[51]),"+f"(d[52]),"+f"(d[53]),"+f"(d[54]),"+f"(d[55])
  : "r"(a0), "r"(a1), "r"(a2), "r"(a3), "l"(desc), "r"(sc));
}
template<> __device__ __forceinline__ void wg_rs<128>(float (&d)[128], uint32_t a0, uint32_t a1, uint32_t a2, uint32_t a3, uint64_t desc, int sc) {
  asm volatile("{\n.reg .pred p;\nsetp.ne.b32 p, %69, 0;\n"
  "wgmma.mma_async.sync.aligned.m64n128k16.f32.bf16.bf16 {%0,%1,%2,%3,%4,%5,%6,%7,%8,%9,%10,%11,%12,%13,%14,%15,%16,%17,%18,%19,%20,%21,%22,%23,%24,%25,%26,%27,%28,%29,%30,%31,%32,%33,%34,%35,%36,%37,%38,%39,%40,%41,%42,%43,%44,%45,%46,%47,%48,%49,%50,%51,%52,%53,%54,%55,%56,%57,%58,%59,%60,%61,%62,%63}, {%64,%65,%66,%67}, %68, p, 1, 1, 0;\n}\n"
  : "+f"(d[0]),"+f"(d[1]),"+f"(d[2]),"+f"(d[3]),"+f"(d[4]),"+f"(d[5]),"+f"(d[6]),"+f"(d[7]),"+f"(d[8]),"+f"(d[9]),"+f"(d[10]),"+f"(d[11]),"+f"(d[12]),"+f"(d[13]),"+f"(d[14]),"+f"(d[15]),"+f"(d[16]),"+f"(d[17]),"+f"(d[18]),"+f"(d[19]),"+f"(d[20]),"+f"(d[21]),"+f"(d[22]),"+f"(d[23]),"+f"(d[24]),"+f"(d[25]),"+f"(d[26]),"+f"(d[27]),"+f"(d[28]),"+f"(d[29]),"+f"(d[30]),"+f"(d[31]),"+f"(d[32]),"+f"(d[33]),"+f"(d[34]),"+f"(d[35]),"+f"(d[36]),"+f"(d[37]),"+f"(d[38]),"+f"(d[39]),"+f"(d[40]),"+f"(d[41]),"+f"(d[42]),"+f"(d[43]),"+f"(d[44]),"+f"(d[45]),"+f"(d[46]),"+f"(d[47]),"+f"(d[48]),"+f"(d[49]),"+f"(d[50]),"+f"(d[51]),"+f"(d[52]),"+f"(d[53]),"+f"(d[54]),"+f"(d[55]),"+f"(d[56]),"+f"(d[57]),"+f"(d[58]),"+f"(d[59]),"+f"(d[60]),"+f"(d[61]),"+f"(d[62]),"+f"(d[63])
  : "r"(a0), "r"(a1), "r"(a2), "r"(a3), "l"(desc), "r"(sc));
}
template<> __device__ __forceinline__ void wg_rs<144>(float (&d)[128], uint32_t a0, uint32_t a1, uint32_t a2, uint32_t a3, uint64_t desc, int sc) {
  asm volatile("{\n.reg .pred p;\nsetp.ne.b32 p, %77, 0;\n"
  "wgmma.mma_async.sync.aligned.m64n144k16.f32.bf16.bf16 {%0,%1,%2,%3,%4,%5,%6,%7,%8,%9,%10,%11,%12,%13,%14,%15,%16,%17,%18,%19,%20,%21,%22,%23,%24,%25,%26,%27,%28,%29,%30,%31,%32,%33,%34,%35,%36,%37,%38,%39,%40,%41,%42,%43,%44,%45,%46,%47,%48,%49,%50,%51,%52,%53,%54,%55,%56,%57,%58,%59,%60,%61,%62,%63,%64,%65,%66,%67,%68,%69,%70,%71}, {%72,%73,%74,%75}, %76, p, 1, 1, 0;\n}\n"
  : "+f"(d[0]),"+f"(d[1]),"+f"(d[2]),"+f"(d[3]),"+f"(d[4]),"+f"(d[5]),"+f"(d[6]),"+f"(d[7]),"+f"(d[8]),"+f"(d[9]),"+f"(d[10]),"+f"(d[11]),"+f"(d[12]),"+f"(d[13]),"+f"(d[14]),"+f"(d[15]),"+f"(d[16]),"+f"(d[17]),"+f"(d[18]),"+f"(d[19]),"+f"(d[20]),"+f"(d[21]),"+f"(d[22]),"+f"(d[23]),"+f"(d[24]),"+f"(d[25]),"+f"(d[26]),"+f"(d[27]),"+f"(d[28]),"+f"(d[29]),"+f"(d[30]),"+f"(d[31]),"+f"(d[32]),"+f"(d[33]),"+f"(d[34]),"+f"(d[35]),"+f"(d[36]),"+f"(d[37]),"+f"(d[38]),"+f"(d[39]),"+f"(d[40]),"+f"(d[41]),"+f"(d[42]),"+f"(d[43]),"+f"(d[44]),"+f"(d[45]),"+f"(d[46]),"+f"(d[47]),"+f"(d[48]),"+f"(d[49]),"+f"(d[50]),"+f"(d[51]),"+f"(d[52]),"+f"(d[53]),"+f"(d[54]),"+f"(d[55]),"+f"(d[56]),"+f"(d[57]),"+f"(d[58]),"+f"(d[59]),"+f"(d[60]),"+f"(d[61]),"+f"(d[62]),"+f"(d[63]),"+f"(d[64]),"+f"(d[65]),"+f"(d[66]),"+f"(d[67]),"+f"(d[68]),"+f"(d[69]),"+f"(d[70]),"+f"(d[71])
  : "r"(a0), "r"(a1), "r"(a2), "r"(a3), "l"(desc), "r"(sc));
}
template<> __device__ __forceinline__ void wg_rs<160>(float (&d)[128], uint32_t a0, uint32_t a1, uint32_t a2, uint32_t a3, uint64_t desc, int sc) {
  asm volatile("{\n.reg .pred p;\nsetp.ne.b32 p, %85, 0;\n"
  "wgmma.mma_async.sync.aligned.m64n160k16.f32.bf16.bf16 {%0,%1,%2,%3,%4,%5,%6,%7,%8,%9,%10,%11,%12,%13,%14,%15,%16,%17,%18,%19,%20,%21,%22,%23,%24,%25,%26,%27,%28,%29,%30,%31,%32,%33,%34,%35,%36,%37,%38,%39,%40,%41,%42,%43,%44,%45,%46,%47,%48,%49,%50,%51,%52,%53,%54,%55,%56,%57,%58,%59,%60,%61,%62,%63,%64,%65,%66,%67,%68,%69,%70,%71,%72,%73,%74,%75,%76,%77,%78,%79}, {%80,%81,%82,%83}, %84, p, 1, 1, 0;\n}\n"
  : "+f"(d[0]),"+f"(d[1]),"+f"(d[2]),"+f"(d[3]),"+f"(d[4]),"+f"(d[5]),"+f"(d[6]),"+f"(d[7]),"+f"(d[8]),"+f"(d[9]),"+f"(d[10]),"+f"(d[11]),"+f"(d[12]),"+f"(d[13]),"+f"(d[14]),"+f"(d[15]),"+f"(d[16]),"+f"(d[17]),"+f"(d[18]),"+f"(d[19]),"+f"(d[20]),"+f"(d[21]),"+f"(d[22]),"+f"(d[23]),"+f"(d[24]),"+f"(d[25]),"+f"(d[26]),"+f"(d[27]),"+f"(d[28]),"+f"(d[29]),"+f"(d[30]),"+f"(d[31]),"+f"(d[32]),"+f"(d[33]),"+f"(d[34]),"+f"(d[35]),"+f"(d[36]),"+f"(d[37]),"+f"(d[38]),"+f"(d[39]),"+f"(d[40]),"+f"(d[41]),"+f"(d[42]),"+f"(d[43]),"+f"(d[44]),"+f"(d[45]),"+f"(d[46]),"+f"(d[47]),"+f"(d[48]),"+f"(d[49]),"+f"(d[50]),"+f"(d[51]),"+f"(d[52]),"+f"(d[53]),"+f"(d[54]),"+f"(d[55]),"+f"(d[56]),"+f"(d[57]),"+f"(d[58]),"+f"(d[59]),"+f"(d[60]),"+f"(d[61]),"+f"(d[62]),"+f"(d[63]),"+f"(d[64]),"+f"(d[65]),"+f"(d[66]),"+f"(d[67]),"+f"(d[68]),"+f"(d[69]),"+f"(d[70]),"+f"(d[71]),"+f"(d[72]),"+f"(d[73]),"+f"(d[74]),"+f"(d[75]),"+f"(d[76]),"+f"(d[77]),"+f"(d[78]),"+f"(d[79])
  : "r"(a0), "r"(a1), "r"(a2), "r"(a3), "l"(desc), "r"(sc));
}
template<> __device__ __forceinline__ void wg_rs<176>(float (&d)[128], uint32_t a0, uint32_t a1, uint32_t a2, uint32_t a3, uint64_t desc, int sc) {
  asm volatile("{\n.reg .pred p;\nsetp.ne.b32 p, %93, 0;\n"
  "wgmma.mma_async.sync.aligned.m64n176k16.f32.bf16.bf16 {%0,%1,%2,%3,%4,%5,%6,%7,%8,%9,%10,%11,%12,%13,%14,%15,%16,%17,%18,%19,%20,%21,%22,%23,%24,%25,%26,%27,%28,%29,%30,%31,%32,%33,%34,%35,%36,%37,%38,%39,%40,%41,%42,%43,%44,%45,%46,%47,%48,%49,%50,%51,%52,%53,%54,%55,%56,%57,%58,%59,%60,%61,%62,%63,%64,%65,%66,%67,%68,%69,%70,%71,%72,%73,%74,%75,%76,%77,%78,%79,%80,%81,%82,%83,%84,%85,%86,%87}, {%88,%89,%90,%91}, %92, p, 1, 1, 0;\n}\n"
  : "+f"(d[0]),"+f"(d[1]),"+f"(d[2]),"+f"(d[3]),"+f"(d[4]),"+f"(d[5]),"+f"(d[6]),"+f"(d[7]),"+f"(d[8]),"+f"(d[9]),"+f"(d[10]),"+f"(d[11]),"+f"(d[12]),"+f"(d[13]),"+f"(d[14]),"+f"(d[15]),"+f"(d[16]),"+f"(d[17]),"+f"(d[18]),"+f"(d[19]),"+f"(d[20]),"+f"(d[21]),"+f"(d[22]),"+f"(d[23]),"+f"(d[24]),"+f"(d[25]),"+f"(d[26]),"+f"(d[27]),"+f"(d[28]),"+f"(d[29]),"+f"(d[30]),"+f"(d[31]),"+f"(d[32]),"+f"(d[33]),"+f"(d[34]),"+f"(d[35]),"+f"(d[36]),"+f"(d[37]),"+f"(d[38]),"+f"(d[39]),"+f"(d[40]),"+f"(d[41]),"+f"(d[42]),"+f"(d[43]),"+f"(d[44]),"+f"(d[45]),"+f"(d[46]),"+f"(d[47]),"+f"(d[48]),"+f"(d[49]),"+f"(d[50]),"+f"(d[51]),"+f"(d[52]),"+f"(d[53]),"+f"(d[54]),"+f"(d[55]),"+f"(d[56]),"+f"(d[57]),"+f"(d[58]),"+f"(d[59]),"+f"(d[60]),"+f"(d[61]),"+f"(d[62]),"+f"(d[63]),"+f"(d[64]),"+f"(d[65]),"+f"(d[66]),"+f"(d[67]),"+f"(d[68]),"+f"(d[69]),"+f"(d[70]),"+f"(d[71]),"+f"(d[72]),"+f"(d[73]),"+f"(d[74]),"+f"(d[75]),"+f"(d[76]),"+f"(d[77]),"+f"(d[78]),"+f"(d[79]),"+f"(d[80]),"+f"(d[81]),"+f"(d[82]),"+f"(d[83]),"+f"(d[84]),"+f"(d[85]),"+f"(d[86]),"+f"(d[87])
  : "r"(a0), "r"(a1), "r"(a2), "r"(a3), "l"(desc), "r"(sc));
}
template<> __device__ __forceinline__ void wg_rs<192>(float (&d)[128], uint32_t a0, uint32_t a1, uint32_t a2, uint32_t a3, uint64_t desc, int sc) {
  asm volatile("{\n.reg .pred p;\nsetp.ne.b32 p, %101, 0;\n"
  "wgmma.mma_async.sync.aligned.m64n192k16.f32.bf16.bf16 {%0,%1,%2,%3,%4,%5,%6,%7,%8,%9,%10,%11,%12,%13,%14,%15,%16,%17,%18,%19,%20,%21,%22,%23,%24,%25,%26,%27,%28,%29,%30,%31,%32,%33,%34,%35,%36,%37,%38,%39,%40,%41,%42,%43,%44,%45,%46,%47,%48,%49,%50,%51,%52,%53,%54,%55,%56,%57,%58,%59,%60,%61,%62,%63,%64,%65,%66,%67,%68,%69,%70,%71,%72,%73,%74,%75,%76,%77,%78,%79,%80,%81,%82,%83,%84,%85,%86,%87,%88,%89,%90,%91,%92,%93,%94,%95}, {%96,%97,%98,%99}, %100, p, 1, 1, 0;\n}\n"
  : "+f"(d[0]),"+f"(d[1]),"+f"(d[2]),"+f"(d[3]),"+f"(d[4]),"+f"(d[5]),"+f"(d[6]),"+f"(d[7]),"+f"(d[8]),"+f"(d[9]),"+f"(d[10]),"+f"(d[11]),"+f"(d[12]),"+f"(d[13]),"+f"(d[14]),"+f"(d[15]),"+f"(d[16]),"+f"(d[17]),"+f"(d[18]),"+f"(d[19]),"+f"(d[20]),"+f"(d[21]),"+f"(d[22]),"+f"(d[23]),"+f"(d[24]),"+f"(d[25]),"+f"(d[26]),"+f"(d[27]),"+f"(d[28]),"+f"(d[29]),"+f"(d[30]),"+f"(d[31]),"+f"(d[32]),"+f"(d[33]),"+f"(d[34]),"+f"(d[35]),"+f"(d[36]),"+f"(d[37]),"+f"(d[38]),"+f"(d[39]),"+f"(d[40]),"+f"(d[41]),"+f"(d[42]),"+f"(d[43]),"+f"(d[44]),"+f"(d[45]),"+f"(d[46]),"+f"(d[47]),"+f"(d[48]),"+f"(d[49]),"+f"(d[50]),"+f"(d[51]),"+f"(d[52]),"+f"(d[53]),"+f"(d[54]),"+f"(d[55]),"+f"(d[56]),"+f"(d[57]),"+f"(d[58]),"+f"(d[59]),"+f"(d[60]),"+f"(d[61]),"+f"(d[62]),"+f"(d[63]),"+f"(d[64]),"+f"(d[65]),"+f"(d[66]),"+f"(d[67]),"+f"(d[68]),"+f"(d[69]),"+f"(d[70]),"+f"(d[71]),"+f"(d[72]),"+f"(d[73]),"+f"(d[74]),"+f"(d[75]),"+f"(d[76]),"+f"(d[77]),"+f"(d[78]),"+f"(d[79]),"+f"(d[80]),"+f"(d[81]),"+f"(d[82]),"+f"(d[83]),"+f"(d[84]),"+f"(d[85]),"+f"(d[86]),"+f"(d[87]),"+f"(d[88]),"+f"(d[89]),"+f"(d[90]),"+f"(d[91]),"+f"(d[92]),"+f"(d[93]),"+f"(d[94]),"+f"(d[95])
  : "r"(a0), "r"(a1), "r"(a2), "r"(a3), "l"(desc), "r"(sc));
}
template<> __device__ __forceinline__ void wg_rs<208>(float (&d)[128], uint32_t a0, uint32_t a1, uint32_t a2, uint32_t a3, uint64_t desc, int sc) {
  asm volatile("{\n.reg .pred p;\nsetp.ne.b32 p, %109, 0;\n"
  "wgmma.mma_async.sync.aligned.m64n208k16.f32.bf16.bf16 {%0,%1,%2,%3,%4,%5,%6,%7,%8,%9,%10,%11,%12,%13,%14,%15,%16,%17,%18,%19,%20,%21,%22,%23,%24,%25,%26,%27,%28,%29,%30,%31,%32,%33,%34,%35,%36,%37,%38,%39,%40,%41,%42,%43,%44,%45,%46,%47,%48,%49,%50,%51,%52,%53,%54,%55,%56,%57,%58,%59,%60,%61,%62,%63,%64,%65,%66,%67,%68,%69,%70,%71,%72,%73,%74,%75,%76,%77,%78,%79,%80,%81,%82,%83,%84,%85,%86,%87,%88,%89,%90,%91,%92,%93,%94,%95,%96,%97,%98,%99,%100,%101,%102,%103}, {%104,%105,%106,%107}, %108, p, 1, 1, 0;\n}\n"
  : "+f"(d[0]),"+f"(d[1]),"+f"(d[2]),"+f"(d[3]),"+f"(d[4]),"+f"(d[5]),"+f"(d[6]),"+f"(d[7]),"+f"(d[8]),"+f"(d[9]),"+f"(d[10]),"+f"(d[11]),"+f"(d[12]),"+f"(d[13]),"+f"(d[14]),"+f"(d[15]),"+f"(d[16]),"+f"(d[17]),"+f"(d[18]),"+f"(d[19]),"+f"(d[20]),"+f"(d[21]),"+f"(d[22]),"+f"(d[23]),"+f"(d[24]),"+f"(d[25]),"+f"(d[26]),"+f"(d[27]),"+f"(d[28]),"+f"(d[29]),"+f"(d[30]),"+f"(d[31]),"+f"(d[32]),"+f"(d[33]),"+f"(d[34]),"+f"(d[35]),"+f"(d[36]),"+f"(d[37]),"+f"(d[38]),"+f"(d[39]),"+f"(d[40]),"+f"(d[41]),"+f"(d[42]),"+f"(d[43]),"+f"(d[44]),"+f"(d[45]),"+f"(d[46]),"+f"(d[47]),"+f"(d[48]),"+f"(d[49]),"+f"(d[50]),"+f"(d[51]),"+f"(d[52]),"+f"(d[53]),"+f"(d[54]),"+f"(d[55]),"+f"(d[56]),"+f"(d[57]),"+f"(d[58]),"+f"(d[59]),"+f"(d[60]),"+f"(d[61]),"+f"(d[62]),"+f"(d[63]),"+f"(d[64]),"+f"(d[65]),"+f"(d[66]),"+f"(d[67]),"+f"(d[68]),"+f"(d[69]),"+f"(d[70]),"+f"(d[71]),"+f"(d[72]),"+f"(d[73]),"+f"(d[74]),"+f"(d[75]),"+f"(d[76]),"+f"(d[77]),"+f"(d[78]),"+f"(d[79]),"+f"(d[80]),"+f"(d[81]),"+f"(d[82]),"+f"(d[83]),"+f"(d[84]),"+f"(d[85]),"+f"(d[86]),"+f"(d[87]),"+f"(d[88]),"+f"(d[89]),"+f"(d[90]),"+f"(d[91]),"+f"(d[92]),"+f"(d[93]),"+f"(d[94]),"+f"(d[95]),"+f"(d[96]),"+f"(d[97]),"+f"(d[98]),"+f"(d[99]),"+f"(d[100]),"+f"(d[101]),"+f"(d[102]),"+f"(d[103])
  : "r"(a0), "r"(a1), "r"(a2), "r"(a3), "l"(desc), "r"(sc));
}
template<> __device__ __forceinline__ void wg_rs<224>(float (&d)[128], uint32_t a0, uint32_t a1, uint32_t a2, uint32_t a3, uint64_t desc, int sc) {
  asm volatile("{\n.reg .pred p;\nsetp.ne.b32 p, %117, 0;\n"
  "wgmma.mma_async.sync.aligned.m64n224k16.f32.bf16.bf16 {%0,%1,%2,%3,%4,%5,%6,%7,%8,%9,%10,%11,%12,%13,%14,%15,%16,%17,%18,%19,%20,%21,%22,%23,%24,%25,%26,%27,%28,%29,%30,%31,%32,%33,%34,%35,%36,%37,%38,%39,%40,%41,%42,%43,%44,%45,%46,%47,%48,%49,%50,%51,%52,%53,%54,%55,%56,%57,%58,%59,%60,%61,%62,%63,%64,%65,%66,%67,%68,%69,%70,%71,%72,%73,%74,%75,%76,%77,%78,%79,%80,%81,%82,%83,%84,%85,%86,%87,%88,%89,%90,%91,%92,%93,%94,%95,%96,%97,%98,%99,%100,%101,%102,%103,%104,%105,%106,%107,%108,%109,%110,%111}, {%112,%113,%114,%115}, %116, p, 1, 1, 0;\n}\n"
  : "+f"(d[0]),"+f"(d[1]),"+f"(d[2]),"+f"(d[3]),"+f"(d[4]),"+f"(d[5]),"+f"(d[6]),"+f"(d[7]),"+f"(d[8]),"+f"(d[9]),"+f"(d[10]),"+f"(d[11]),"+f"(d[12]),"+f"(d[13]),"+f"(d[14]),"+f"(d[15]),"+f"(d[16]),"+f"(d[17]),"+f"(d[18]),"+f"(d[19]),"+f"(d[20]),"+f"(d[21]),"+f"(d[22]),"+f"(d[23]),"+f"(d[24]),"+f"(d[25]),"+f"(d[26]),"+f"(d[27]),"+f"(d[28]),"+f"(d[29]),"+f"(d[30]),"+f"(d[31]),"+f"(d[32]),"+f"(d[33]),"+f"(d[34]),"+f"(d[35]),"+f"(d[36]),"+f"(d[37]),"+f"(d[38]),"+f"(d[39]),"+f"(d[40]),"+f"(d[41]),"+f"(d[42]),"+f"(d[43]),"+f"(d[44]),"+f"(d[45]),"+f"(d[46]),"+f"(d[47]),"+f"(d[48]),"+f"(d[49]),"+f"(d[50]),"+f"(d[51]),"+f"(d[52]),"+f"(d[53]),"+f"(d[54]),"+f"(d[55]),"+f"(d[56]),"+f"(d[57]),"+f"(d[58]),"+f"(d[59]),"+f"(d[60]),"+f"(d[61]),"+f"(d[62]),"+f"(d[63]),"+f"(d[64]),"+f"(d[65]),"+f"(d[66]),"+f"(d[67]),"+f"(d[68]),"+f"(d[69]),"+f"(d[70]),"+f"(d[71]),"+f"(d[72]),"+f"(d[73]),"+f"(d[74]),"+f"(d[75]),"+f"(d[76]),"+f"(d[77]),"+f"(d[78]),"+f"(d[79]),"+f"(d[80]),"+f"(d[81]),"+f"(d[82]),"+f"(d[83]),"+f"(d[84]),"+f"(d[85]),"+f"(d[86]),"+f"(d[87]),"+f"(d[88]),"+f"(d[89]),"+f"(d[90]),"+f"(d[91]),"+f"(d[92]),"+f"(d[93]),"+f"(d[94]),"+f"(d[95]),"+f"(d[96]),"+f"(d[97]),"+f"(d[98]),"+f"(d[99]),"+f"(d[100]),"+f"(d[101]),"+f"(d[102]),"+f"(d[103]),"+f"(d[104]),"+f"(d[105]),"+f"(d[106]),"+f"(d[107]),"+f"(d[108]),"+f"(d[109]),"+f"(d[110]),"+f"(d[111])
  : "r"(a0), "r"(a1), "r"(a2), "r"(a3), "l"(desc), "r"(sc));
}
template<> __device__ __forceinline__ void wg_rs<240>(float (&d)[128], uint32_t a0, uint32_t a1, uint32_t a2, uint32_t a3, uint64_t desc, int sc) {
  asm volatile("{\n.reg .pred p;\nsetp.ne.b32 p, %125, 0;\n"
  "wgmma.mma_async.sync.aligned.m64n240k16.f32.bf16.bf16 {%0,%1,%2,%3,%4,%5,%6,%7,%8,%9,%10,%11,%12,%13,%14,%15,%16,%17,%18,%19,%20,%21,%22,%23,%24,%25,%26,%27,%28,%29,%30,%31,%32,%33,%34,%35,%36,%37,%38,%39,%40,%41,%42,%43,%44,%45,%46,%47,%48,%49,%50,%51,%52,%53,%54,%55,%56,%57,%58,%59,%60,%61,%62,%63,%64,%65,%66,%67,%68,%69,%70,%71,%72,%73,%74,%75,%76,%77,%78,%79,%80,%81,%82,%83,%84,%85,%86,%87,%88,%89,%90,%91,%92,%93,%94,%95,%96,%97,%98,%99,%100,%101,%102,%103,%104,%105,%106,%107,%108,%109,%110,%111,%112,%113,%114,%115,%116,%117,%118,%119}, {%120,%121,%122,%123}, %124, p, 1, 1, 0;\n}\n"
  : "+f"(d[0]),"+f"(d[1]),"+f"(d[2]),"+f"(d[3]),"+f"(d[4]),"+f"(d[5]),"+f"(d[6]),"+f"(d[7]),"+f"(d[8]),"+f"(d[9]),"+f"(d[10]),"+f"(d[11]),"+f"(d[12]),"+f"(d[13]),"+f"(d[14]),"+f"(d[15]),"+f"(d[16]),"+f"(d[17]),"+f"(d[18]),"+f"(d[19]),"+f"(d[20]),"+f"(d[21]),"+f"(d[22]),"+f"(d[23]),"+f"(d[24]),"+f"(d[25]),"+f"(d[26]),"+f"(d[27]),"+f"(d[28]),"+f"(d[29]),"+f"(d[30]),"+f"(d[31]),"+f"(d[32]),"+f"(d[33]),"+f"(d[34]),"+f"(d[35]),"+f"(d[36]),"+f"(d[37]),"+f"(d[38]),"+f"(d[39]),"+f"(d[40]),"+f"(d[41]),"+f"(d[42]),"+f"(d[43]),"+f"(d[44]),"+f"(d[45]),"+f"(d[46]),"+f"(d[47]),"+f"(d[48]),"+f"(d[49]),"+f"(d[50]),"+f"(d[51]),"+f"(d[52]),"+f"(d[53]),"+f"(d[54]),"+f"(d[55]),"+f"(d[56]),"+f"(d[57]),"+f"(d[58]),"+f"(d[59]),"+f"(d[60]),"+f"(d[61]),"+f"(d[62]),"+f"(d[63]),"+f"(d[64]),"+f"(d[65]),"+f"(d[66]),"+f"(d[67]),"+f"(d[68]),"+f"(d[69]),"+f"(d[70]),"+f"(d[71]),"+f"(d[72]),"+f"(d[73]),"+f"(d[74]),"+f"(d[75]),"+f"(d[76]),"+f"(d[77]),"+f"(d[78]),"+f"(d[79]),"+f"(d[80]),"+f"(d[81]),"+f"(d[82]),"+f"(d[83]),"+f"(d[84]),"+f"(d[85]),"+f"(d[86]),"+f"(d[87]),"+f"(d[88]),"+f"(d[89]),"+f"(d[90]),"+f"(d[91]),"+f"(d[92]),"+f"(d[93]),"+f"(d[94]),"+f"(d[95]),"+f"(d[96]),"+f"(d[97]),"+f"(d[98]),"+f"(d[99]),"+f"(d[100]),"+f"(d[101]),"+f"(d[102]),"+f"(d[103]),"+f"(d[104]),"+f"(d[105]),"+f"(d[106]),"+f"(d[107]),"+f"(d[108]),"+f"(d[109]),"+f"(d[110]),"+f"(d[111]),"+f"(d[112]),"+f"(d[113]),"+f"(d[114]),"+f"(d[115]),"+f"(d[116]),"+f"(d[117]),"+f"(d[118]),"+f"(d[119])
  : "r"(a0), "r"(a1), "r"(a2), "r"(a3), "l"(desc), "r"(sc));
}
template<> __device__ __forceinline__ void wg_rs<256>(float (&d)[128], uint32_t a0, uint32_t a1, uint32_t a2, uint32_t a3, uint64_t desc, int sc) {
  asm volatile("{\n.reg .pred p;\nsetp.ne.b32 p, %133, 0;\n"
  "wgmma.mma_async.sync.aligned.m64n256k16.f32.bf16.bf16 {%0,%1,%2,%3,%4,%5,%6,%7,%8,%9,%10,%11,%12,%13,%14,%15,%16,%17,%18,%19,%20,%21,%22,%23,%24,%25,%26,%27,%28,%29,%30,%31,%32,%33,%34,%35,%36,%37,%38,%39,%40,%41,%42,%43,%44,%45,%46,%47,%48,%49,%50,%51,%52,%53,%54,%55,%56,%57,%58,%59,%60,%61,%62,%63,%64,%65,%66,%67,%68,%69,%70,%71,%72,%73,%74,%75,%76,%77,%78,%79,%80,%81,%82,%83,%84,%85,%86,%87,%88,%89,%90,%91,%92,%93,%94,%95,%96,%97,%98,%99,%100,%101,%102,%103,%104,%105,%106,%107,%108,%109,%110,%111,%112,%113,%114,%115,%116,%117,%118,%119,%120,%121,%122,%123,%124,%125,%126,%127}, {%128,%129,%130,%131}, %132, p, 1, 1, 0;\n}\n"
  : "+f"(d[0]),"+f"(d[1]),"+f"(d[2]),"+f"(d[3]),"+f"(d[4]),"+f"(d[5]),"+f"(d[6]),"+f"(d[7]),"+f"(d[8]),"+f"(d[9]),"+f"(d[10]),"+f"(d[11]),"+f"(d[12]),"+f"(d[13]),"+f"(d[14]),"+f"(d[15]),"+f"(d[16]),"+f"(d[17]),"+f"(d[18]),"+f"(d[19]),"+f"(d[20]),"+f"(d[21]),"+f"(d[22]),"+f"(d[23]),"+f"(d[24]),"+f"(d[25]),"+f"(d[26]),"+f"(d[27]),"+f"(d[28]),"+f"(d[29]),"+f"(d[30]),"+f"(d[31]),"+f"(d[32]),"+f"(d[33]),"+f"(d[34]),"+f"(d[35]),"+f"(d[36]),"+f"(d[37]),"+f"(d[38]),"+f"(d[39]),"+f"(d[40]),"+f"(d[41]),"+f"(d[42]),"+f"(d[43]),"+f"(d[44]),"+f"(d[45]),"+f"(d[46]),"+f"(d[47]),"+f"(d[48]),"+f"(d[49]),"+f"(d[50]),"+f"(d[51]),"+f"(d[52]),"+f"(d[53]),"+f"(d[54]),"+f"(d[55]),"+f"(d[56]),"+f"(d[57]),"+f"(d[58]),"+f"(d[59]),"+f"(d[60]),"+f"(d[61]),"+f"(d[62]),"+f"(d[63]),"+f"(d[64]),"+f"(d[65]),"+f"(d[66]),"+f"(d[67]),"+f"(d[68]),"+f"(d[69]),"+f"(d[70]),"+f"(d[71]),"+f"(d[72]),"+f"(d[73]),"+f"(d[74]),"+f"(d[75]),"+f"(d[76]),"+f"(d[77]),"+f"(d[78]),"+f"(d[79]),"+f"(d[80]),"+f"(d[81]),"+f"(d[82]),"+f"(d[83]),"+f"(d[84]),"+f"(d[85]),"+f"(d[86]),"+f"(d[87]),"+f"(d[88]),"+f"(d[89]),"+f"(d[90]),"+f"(d[91]),"+f"(d[92]),"+f"(d[93]),"+f"(d[94]),"+f"(d[95]),"+f"(d[96]),"+f"(d[97]),"+f"(d[98]),"+f"(d[99]),"+f"(d[100]),"+f"(d[101]),"+f"(d[102]),"+f"(d[103]),"+f"(d[104]),"+f"(d[105]),"+f"(d[106]),"+f"(d[107]),"+f"(d[108]),"+f"(d[109]),"+f"(d[110]),"+f"(d[111]),"+f"(d[112]),"+f"(d[113]),"+f"(d[114]),"+f"(d[115]),"+f"(d[116]),"+f"(d[117]),"+f"(d[118]),"+f"(d[119]),"+f"(d[120]),"+f"(d[121]),"+f"(d[122]),"+f"(d[123]),"+f"(d[124]),"+f"(d[125]),"+f"(d[126]),"+f"(d[127])
  : "r"(a0), "r"(a1), "r"(a2), "r"(a3), "l"(desc), "r"(sc));
}

__device__ __forceinline__ void wg_fence() { asm volatile("wgmma.fence.sync.aligned;" ::: "memory"); }
__device__ __forceinline__ void wg_commit() { asm volatile("wgmma.commit_group.sync.aligned;" ::: "memory"); }
template <int N> __device__ __forceinline__ void wg_wait() { asm volatile("wgmma.wait_group.sync.aligned %0;" ::"n"(N) : "memory"); }
__device__ __forceinline__ void fence_async() { asm volatile("fence.proxy.async.shared::cta;" ::: "memory"); }
__device__ __forceinline__ void bar_sync(int id, int n) { asm volatile("bar.sync %0, %1;" ::"r"(id), "r"(n) : "memory"); }
__device__ __forceinline__ void bar_arrive(int id, int n) { asm volatile("bar.arrive %0, %1;" ::"r"(id), "r"(n) : "memory"); }
__device__ __forceinline__ uint32_t lds16(uint32_t a) { unsigned short v; asm volatile("ld.shared.b16 %0, [%1];" : "=h"(v) : "r"(a)); return v; }
__device__ __forceinline__ uint32_t lds32(uint32_t a) { uint32_t v; asm volatile("ld.shared.b32 %0, [%1];" : "=r"(v) : "r"(a)); return v; }
__device__ __forceinline__ void lds32p(uint32_t& v, uint32_t a, int p) { asm volatile("{\n.reg .pred q;\nsetp.ne.b32 q, %2, 0;\n@q ld.shared.b32 %0, [%1];\n}\n" : "+r"(v) : "r"(a), "r"(p)); }
__device__ __forceinline__ uint2 lds64(uint32_t a) { uint2 v; asm volatile("ld.shared.v2.b32 {%0,%1}, [%2];" : "=r"(v.x), "=r"(v.y) : "r"(a)); return v; }
__device__ __forceinline__ uint4 lds128(uint32_t a) { uint4 v; asm volatile("ld.shared.v4.b32 {%0,%1,%2,%3}, [%4];" : "=r"(v.x), "=r"(v.y), "=r"(v.z), "=r"(v.w) : "r"(a)); return v; }
__device__ __forceinline__ void sts32(uint32_t a, uint32_t v) { asm volatile("st.shared.b32 [%0], %1;" ::"r"(a), "r"(v) : "memory"); }
__device__ __forceinline__ void sts16(uint32_t a, uint32_t v) { asm volatile("st.shared.b16 [%0], %1;" ::"r"(a), "h"((unsigned short)v) : "memory"); }
__device__ __forceinline__ void sts128(uint32_t a, uint32_t x, uint32_t y, uint32_t z, uint32_t w) { asm volatile("st.shared.v4.b32 [%0], {%1,%2,%3,%4};" ::"r"(a), "r"(x), "r"(y), "r"(z), "r"(w) : "memory"); }
__device__ __forceinline__ void ldsm4(uint32_t (&r)[4], uint32_t a) { asm volatile("ldmatrix.sync.aligned.m8n8.x4.shared.b16 {%0,%1,%2,%3}, [%4];" : "=r"(r[0]), "=r"(r[1]), "=r"(r[2]), "=r"(r[3]) : "r"(a)); }
__device__ __forceinline__ void ldsm4t(uint32_t (&r)[4], uint32_t a) { asm volatile("ldmatrix.sync.aligned.m8n8.x4.trans.shared.b16 {%0,%1,%2,%3}, [%4];" : "=r"(r[0]), "=r"(r[1]), "=r"(r[2]), "=r"(r[3]) : "r"(a)); }
__device__ __forceinline__ void ldsm2t(uint32_t& r0, uint32_t& r1, uint32_t a) { asm volatile("ldmatrix.sync.aligned.m8n8.x2.trans.shared.b16 {%0,%1}, [%2];" : "=r"(r0), "=r"(r1) : "r"(a)); }
__device__ __forceinline__ void stsm4t(uint32_t a, uint32_t r0, uint32_t r1, uint32_t r2, uint32_t r3) { asm volatile("stmatrix.sync.aligned.m8n8.x4.trans.shared.b16 [%0], {%1,%2,%3,%4};" ::"r"(a), "r"(r0), "r"(r1), "r"(r2), "r"(r3) : "memory"); }
__device__ __forceinline__ void stsm4(uint32_t a, const uint32_t (&r)[4]) { asm volatile("stmatrix.sync.aligned.m8n8.x4.shared.b16 [%0], {%1,%2,%3,%4};" ::"r"(a), "r"(r[0]), "r"(r[1]), "r"(r[2]), "r"(r[3]) : "memory"); }
__device__ __forceinline__ void tma_store(const CUtensorMap* m, uint32_t src, int c0, int c1) {
  asm volatile("cp.async.bulk.tensor.2d.global.shared::cta.bulk_group [%0, {%2, %3}], [%1];" ::"l"(m), "r"(src), "r"(c0), "r"(c1) : "memory");
}
__device__ __forceinline__ uint32_t mapa(uint32_t a, uint32_t rank) { uint32_t r; asm("mapa.shared::cluster.u32 %0, %1, %2;" : "=r"(r) : "r"(a), "r"(rank)); return r; }
__device__ __forceinline__ void st_async4(uint32_t a, uint32_t x, uint32_t y, uint32_t z, uint32_t w, uint32_t mbar) {
  asm volatile("st.async.weak.shared::cluster.mbarrier::complete_tx::bytes.v4.b32 [%0], {%1,%2,%3,%4}, [%5];" ::"r"(a), "r"(x), "r"(y), "r"(z), "r"(w), "r"(mbar) : "memory");
}
__device__ __forceinline__ void st_async1(uint32_t a, uint32_t x, uint32_t mbar) {
  asm volatile("st.async.weak.shared::cluster.mbarrier::complete_tx::bytes.b32 [%0], %1, [%2];" ::"r"(a), "r"(x), "r"(mbar) : "memory");
}
__device__ __forceinline__ void mbar_init(uint32_t b, uint32_t n) { asm volatile("mbarrier.init.shared::cta.b64 [%0], %1;" ::"r"(b), "r"(n) : "memory"); }
__device__ __forceinline__ void mbar_expect(uint32_t b, uint32_t bytes) { asm volatile("mbarrier.arrive.expect_tx.shared::cta.b64 _, [%0], %1;" ::"r"(b), "r"(bytes) : "memory"); }
__device__ __forceinline__ void mbar_arrive(uint32_t b) { asm volatile("mbarrier.arrive.shared::cta.b64 _, [%0];" ::"r"(b) : "memory"); }
__device__ __forceinline__ void mbar_wait(uint32_t b) {
  asm volatile("{\n.reg .pred p, q;\n.reg .u32 n;\nmov.u32 n, 0;\nWAIT_LOOP:\n"
               "mbarrier.try_wait.parity.shared::cta.b64 p, [%0], 0, 100000;\n@p bra WAIT_DONE;\n"
               "add.u32 n, n, 1;\nsetp.lt.u32 q, n, 4194304;\n@q bra WAIT_LOOP;\ntrap;\nWAIT_DONE:\n}\n" ::"r"(b) : "memory");
}
__device__ __forceinline__ void tma4(uint32_t dst, const CUtensorMap* m, int c0, int c3, uint32_t mbar) {
  asm volatile("cp.async.bulk.tensor.4d.shared::cluster.global.mbarrier::complete_tx::bytes [%0], [%1, {%3, %4, %4, %5}], [%2];" ::"r"(dst), "l"(m), "r"(mbar), "r"(c0), "r"(0), "r"(c3) : "memory");
}
__device__ __forceinline__ uint32_t prmt(uint32_t a, uint32_t b, uint32_t s) { uint32_t r; asm("prmt.b32 %0, %1, %2, %3;" : "=r"(r) : "r"(a), "r"(b), "r"(s)); return r; }
__device__ __forceinline__ uint32_t hmul(uint32_t a, uint32_t b) { uint32_t r; asm("mul.rn.bf16x2 %0, %1, %2;" : "=r"(r) : "r"(a), "r"(b)); return r; }
__device__ __forceinline__ uint32_t hadd(uint32_t a, uint32_t b) { uint32_t r; asm("add.rn.bf16x2 %0, %1, %2;" : "=r"(r) : "r"(a), "r"(b)); return r; }
__device__ __forceinline__ uint32_t hfma(uint32_t a, uint32_t b, uint32_t c) { uint32_t r; asm("fma.rn.bf16x2 %0, %1, %2, %3;" : "=r"(r) : "r"(a), "r"(b), "r"(c)); return r; }
__device__ __forceinline__ void mma16(float (&d)[4], const uint32_t (&a)[4], uint32_t b0, uint32_t b1) {
  asm volatile("mma.sync.aligned.m16n8k16.row.col.f32.bf16.bf16.f32 {%0,%1,%2,%3}, {%4,%5,%6,%7}, {%8,%9}, {%0,%1,%2,%3};"
               : "+f"(d[0]), "+f"(d[1]), "+f"(d[2]), "+f"(d[3]) : "r"(a[0]), "r"(a[1]), "r"(a[2]), "r"(a[3]), "r"(b0), "r"(b1));
}
__device__ __forceinline__ void mma8(float (&d)[4], uint32_t a0, uint32_t a1, uint32_t b0) {
  asm volatile("mma.sync.aligned.m16n8k8.row.col.f32.bf16.bf16.f32 {%0,%1,%2,%3}, {%4,%5}, {%6}, {%0,%1,%2,%3};"
               : "+f"(d[0]), "+f"(d[1]), "+f"(d[2]), "+f"(d[3]) : "r"(a0), "r"(a1), "r"(b0));
}
__device__ __forceinline__ uint32_t pack_bf(float lo, float hi) { uint32_t r; asm("cvt.rn.bf16x2.f32 %0, %1, %2;" : "=r"(r) : "f"(hi), "f"(lo)); return r; }
__device__ __forceinline__ __half2 pack_h(float lo, float hi) { return __floats2half2_rn(lo, hi); }
__device__ __forceinline__ float bf_lo(uint32_t v) { return __uint_as_float(v << 16); }
__device__ __forceinline__ float rbf(float x) { return bf_lo(pack_bf(x, 0.f)); }

struct Params {
  const bf16* s4[4];
  const bf16 *shift_k, *ssm_k, *ssm_D, *ldt, *dskip, *gate_w;
  unsigned int *gate_part, *epoch;
};

struct cplx { float r, i; };
__device__ __forceinline__ cplx cmul(cplx a, cplx b) { cplx c; c.r = fmaf(a.r, b.r, -a.i * b.i); c.i = fmaf(a.r, b.i, a.i * b.r); return c; }
__device__ __forceinline__ cplx csqr(cplx a) { cplx c; c.r = fmaf(a.r, a.r, -a.i * a.i); c.i = (a.r + a.r) * a.i; return c; }
__device__ __forceinline__ cplx cexp_p(float ar, float ai, float p) {
  float m; asm("ex2.approx.ftz.f32 %0, %1;" : "=f"(m) : "f"(ar * (p * 1.4426950408889634f)));
  float ph = ai * p;
  const float k = rintf(ph * 0.15915494309189535f);
  ph = fmaf(-k, 6.2831854820251465f, ph);
  ph = fmaf(-k, -1.7484555314695172e-07f, ph);
  cplx c; c.r = m * __cosf(ph); c.i = m * __sinf(ph); return c;
}
struct hv { __half2 r, i; };
__device__ __forceinline__ hv hcmul(hv x, __half2 e) {
  const __half2 er = __low2half2(e), ei = __high2half2(e);
  hv y; y.r = __hfma2(x.r, er, __hneg2(__hmul2(x.i, ei))); y.i = __hfma2(x.r, ei, __hmul2(x.i, er)); return y;
}
__device__ __forceinline__ uint32_t h2u(__half2 h) { return *reinterpret_cast<uint32_t*>(&h); }
__device__ __forceinline__ hv lows(hv a, hv b) { hv y; y.r = __lows2half2(a.r, b.r); y.i = __lows2half2(a.i, b.i); return y; }
__device__ __forceinline__ void put_group(uint32_t a, const hv& v0, const hv& v1, const hv& v2, const hv& v3) {
  sts128(a, h2u(v0.r), h2u(v1.r), h2u(v2.r), h2u(v3.r));
  sts128(a + 256, h2u(v0.i), h2u(v1.i), h2u(v2.i), h2u(v3.i));
}
struct KSetup { hv v0, x0; __half2 e2, e4, e16, e32, e64, e128, e256, e512, e1k; };
__device__ __forceinline__ KSetup ksetup(uint32_t par, int n) {
  const uint32_t pn = par + 2 * n;
  const uint4 sc = lds128(par + 1024);
  const float dt = __uint_as_float(sc.x), sdn = __uint_as_float(sc.z);
  const float ar = -rbf(expf(bf_lo(lds16(pn)))) * dt;
  const float ai = bf_lo(lds16(pn + 256)) * dt;
  cplx C; C.r = bf_lo(lds16(pn + 512)) * sdn; C.i = bf_lo(lds16(pn + 768)) * sdn;
  const cplx E1 = cexp_p(ar, ai, 1.f), E64 = cexp_p(ar, ai, 64.f);
  const cplx E2 = csqr(E1), E4 = csqr(E2), E8 = csqr(E4), E16 = csqr(E8), E32 = csqr(E16);
  const cplx E128 = csqr(E64), E256 = csqr(E128), E512 = csqr(E256), E1k = csqr(E512);
  const cplx C1 = cmul(C, E1);
  KSetup s;
  s.v0.r = pack_h(1.f, E8.r); s.v0.i = pack_h(0.f, E8.i);
  s.x0.r = pack_h(C.r, C1.r); s.x0.i = pack_h(C.i, C1.i);
  s.e2 = pack_h(E2.r, E2.i); s.e4 = pack_h(E4.r, E4.i); s.e16 = pack_h(E16.r, E16.i); s.e32 = pack_h(E32.r, E32.i);
  s.e64 = pack_h(E64.r, E64.i); s.e128 = pack_h(E128.r, E128.i); s.e256 = pack_h(E256.r, E256.i); s.e512 = pack_h(E512.r, E512.i);
  s.e1k = pack_h(E1k.r, E1k.i);
  return s;
}
__device__ __forceinline__ void kstage(const KSetup& s, uint32_t sb, uint32_t sn) {
  hv v[8], z[4];
  v[0] = s.v0;
  v[1] = hcmul(v[0], s.e16);
  v[2] = hcmul(v[0], s.e32); v[3] = hcmul(v[1], s.e32);
#pragma unroll
  for (int i = 0; i < 4; i++) v[4 + i] = hcmul(v[i], s.e64);
#pragma unroll
  for (int i = 0; i < 4; i++) z[i] = hcmul(v[i], s.e128);
  put_group(sb + 4096, z[0], z[1], z[2], z[3]);
  put_group(sb, v[0], v[1], v[2], v[3]);
#pragma unroll
  for (int i = 0; i < 4; i++) z[i] = hcmul(v[4 + i], s.e128);
  put_group(sb + 6144, z[0], z[1], z[2], z[3]);
  put_group(sb + 2048, v[4], v[5], v[6], v[7]);
  const hv x0 = s.x0, x1 = hcmul(x0, s.e2), x2 = hcmul(x0, s.e4), x3 = hcmul(x1, s.e4);
  const hv y0 = hcmul(lows(x0, x1), s.e256), y1 = hcmul(lows(x2, x3), s.e256);
  const hv y2 = hcmul(lows(x0, x2), s.e512), y3 = hcmul(lows(y0, y1), s.e512);
  const hv z0 = hcmul(lows(x0, y0), s.e1k), z1 = hcmul(lows(y2, y3), s.e1k), z2 = hcmul(z0, s.e1k);
  put_group(sn, x0, x1, x2, x3);
  put_group(sn + 2048, y0, y1, y2, y3);
  put_group(sn + 4096, z0, z1, z2, z2);
}
template <int KS> __device__ __forceinline__ void kmma(float (&d)[24], uint64_t da) {
  if constexpr (KS < 8) {
    const uint64_t a = da + (uint64_t)(KS * 16);
    asm volatile("{\n.reg .pred p;\nsetp.ne.b32 p, %26, 0;\n"
                 "wgmma.mma_async.sync.aligned.m64n48k16.f32.f16.f16 {%0,%1,%2,%3,%4,%5,%6,%7,%8,%9,%10,%11,%12,%13,%14,%15,%16,%17,%18,%19,%20,%21,%22,%23}, %24, %25, p, %27, 1, 1, 1;\n}\n"
                 : "+f"(d[0]), "+f"(d[1]), "+f"(d[2]), "+f"(d[3]), "+f"(d[4]), "+f"(d[5]), "+f"(d[6]), "+f"(d[7]), "+f"(d[8]), "+f"(d[9]), "+f"(d[10]), "+f"(d[11]), "+f"(d[12]), "+f"(d[13]), "+f"(d[14]), "+f"(d[15]), "+f"(d[16]), "+f"(d[17]), "+f"(d[18]), "+f"(d[19]), "+f"(d[20]), "+f"(d[21]), "+f"(d[22]), "+f"(d[23])
                 : "l"(a), "l"(a + 1024), "r"(KS > 0 ? 1 : 0), "n"((KS & 1) ? -1 : 1));
    kmma<KS + 1>(d, da);
  }
}
__device__ __forceinline__ void kcompact(const float* d, float sc, float skip, uint32_t a0, uint32_t a1, uint32_t a1h, uint32_t a2, bool lo, bool top) {
  sts32(a0, pack_bf(fmaf(d[0], sc, skip), d[1] * sc));
  sts32(a0 + 128, pack_bf(d[2] * sc, d[3] * sc));
  sts32(a1, pack_bf(d[4] * sc, d[5] * sc));
  sts32(a1h, pack_bf(d[6] * sc, d[7] * sc));
  const uint32_t p0 = pack_bf(d[8] * sc, d[9] * sc), p1 = pack_bf(d[10] * sc, d[11] * sc);
  if (lo || top) sts16(a2, p0);
  if (lo) { sts16(a2 + 64, p0 >> 16); sts16(a2 + 16, p1); sts16(a2 + 80, p1 >> 16); }
}
__device__ __forceinline__ uint32_t cmp32(uint32_t a) { return hadd(lds32(a), lds32(a + CMP_H)); }

template <int M, int MEND> __device__ __forceinline__ void mma_steps(float (&d)[128], const uint32_t (&a)[64], uint64_t desc) {
  if constexpr (M < MEND) {
    wg_rs<256 - 16 * M>(d, a[4 * M], a[4 * M + 1], a[4 * M + 2], a[4 * M + 3], desc + (uint64_t)(16 * M), M > 0);
    mma_steps<M + 1, MEND>(d, a, desc);
  }
}
#define TAPOFF(i) (2 * (128 * ((i) >> 2) + ((i) & 1) * 64 + (((i) >> 1) & 1) * 8))

template <bool IS_B>
__device__ __forceinline__ void conv_unit(uint32_t (&a)[64], uint32_t sm, int u, int wg, int w, int lane, int rank, uint32_t ta) {
  const uint32_t scr = sm + SCR + wg * SCR_SZ, t16 = 512 * w + 16 * lane;
  const uint64_t desc = (uint64_t)((((sm + UB) & 0x3FFFF) >> 4) + u * (UB_SZ / 16)) | ((uint64_t)1 << 16) | ((uint64_t)8 << 32);
  const int more = IS_B || u < 8;
  const uint32_t tb = ta + (u + 2) * TAB_SZ;
  float d[128];
  TS(wg * 32 + 3 + 3 * (u >> 1));
  bar_sync(NB_TURN + wg, 256);
  wg_fence();
  mma_steps<0, 8>(d, a, desc);
  wg_commit();
  mma_steps<8, 16>(d, a, desc);
  wg_commit();
  if (IS_B || u < 9) bar_arrive(NB_TURN + (wg ^ 1), 256);
  TS(wg * 32 + 4 + 3 * (u >> 1));
  if (IS_B && u >= 3) { mbar_wait(sm + BARS + 8 * B_KVT); fence_async(); }
  if (!IS_B && u < 7) mbar_wait(sm + BARS + 8 * B_G);
  if (more && u >= 3) bar_sync(NB_TAB - 3 + u, 256);
  wg_wait<1>();
#pragma unroll
  for (int i = 0; i < 32; i++) lds32p(a[i], tb + TAPOFF(i), more);
  wg_wait<0>();
  TS(wg * 32 + 5 + 3 * (u >> 1));
  const uint32_t pl = scr + w * PLANE + 16 * lane;
#pragma unroll
  for (int jq = 0; jq < 8; jq++) {
    uint32_t p[4];
#pragma unroll
    for (int m = 0; m < 4; m++) {
      const int j = 4 * jq + m;
      p[m] = j < 31 ? pack_bf(d[4 * j] + d[4 * j + 6], d[4 * j + 1] + d[4 * j + 7]) : pack_bf(d[4 * j], d[4 * j + 1]);
    }
    stsm4t(pl + jq * 512, p[0], p[1], p[2], p[3]);
#pragma unroll
    for (int i = 32 + 4 * jq; i < 36 + 4 * jq; i++) lds32p(a[i], tb + TAPOFF(i), more);
  }
  const uint32_t yb = sm + TAB + (IS_B ? u : u - 5) * TAB_SZ + t16;
  uint4 q4[2], g4[2], b4[2];
  if (!IS_B) {
#pragma unroll
    for (int hf = 0; hf < 2; hf++) {
      q4[hf] = lds128(sm + UB + (u - 5) * UB_SZ + t16 + 2048 * hf);
      b4[hf] = lds128(yb + 2048 * hf);
      g4[hf] = lds128(sm + GBUF + t16 + 2048 * hf);
    }
  }
  bar_sync(NB_WG + wg, 128);
  uint4 pz[2][4];
#pragma unroll
  for (int hf = 0; hf < 2; hf++)
#pragma unroll
    for (int k = 3; k >= 0; k--) pz[hf][k] = lds128(scr + k * (PLANE + 32) + t16 + 2048 * hf);
#define PSUM(hf, f) hadd(hadd(hadd(pz[hf][3].f, pz[hf][2].f), pz[hf][1].f), pz[hf][0].f)
#define MIX(hf, f) hfma(g4[hf].f, hfma(q4[hf].f, PSUM(hf, f), b4[hf].f), b4[hf].f)
  if (IS_B) {
    sts128(yb, PSUM(0, x), PSUM(0, y), PSUM(0, z), PSUM(0, w));
    sts128(yb + 2048, PSUM(1, x), PSUM(1, y), PSUM(1, z), PSUM(1, w));
  } else {
#pragma unroll
    for (int hf = 0; hf < 2; hf++) {
      const uint32_t rb = mapa(sm, 7 - (w + 4 * hf));
      st_async4(rb + RECV + (u - 5) * RECV_SZ + rank * RECV_PITCH + 16 * lane, MIX(hf, x), MIX(hf, y), MIX(hf, z), MIX(hf, w), rb + BARS + 8 * (B_O - 5 + u));
    }
  }
#undef PSUM
#undef MIX
  TS(wg * 32 + 20 + (u >> 1));
}

__global__ void __launch_bounds__(384, 1)
fused_kernel(const __grid_constant__ CUtensorMap mq, const __grid_constant__ CUtensorMap mk, const __grid_constant__ CUtensorMap mv,
             const __grid_constant__ CUtensorMap mo8, const __grid_constant__ CUtensorMap mo16, const __grid_constant__ Params P) {
  extern __shared__ __align__(1024) uint8_t smem[];
  const uint32_t sm = (uint32_t)__cvta_generic_to_shared(smem);
  const int tid = threadIdx.x, lane = tid & 31;
  const int cl = blockIdx.x >> 3, rank = blockIdx.x & 7;
  const int ch0 = min(cl * RMAX * 8, D_CH - RMAX * 8);
  const int ev = ((ch0 >> 3) & 1) ^ 1;
#define GO(r) ((r) == 0 ? 4 * ev : (r) - ev)
  const uint32_t bars = sm + BARS;
  TS((tid >> 7) * 32 + 0); TG(82);
  uint4 pv = make_uint4(0, 0, 0, 0);
  if (tid < 320) {
    pv = __ldg((const uint4*)(P.s4[(tid >> 4) & 3] + (ch0 + 8 * GO(tid >> 6) + rank) * NST) + (tid & 15));
  } else if (tid < 352) {
    const uint4* src = lane < 8 ? (const uint4*)(P.gate_w + ch0) + lane : (const uint4*)(P.shift_k + ch0 * 4) + (lane - 8);
    if ((lane < RMAX && ch0 + 8 * lane >= cl * RMAX * 8) || (lane >= 8 && lane < 8 + 4 * RMAX)) pv = __ldg(src);
  } else {
    const int ch = ch0 + 8 * GO(min(lane, RMAX - 1)) + rank;
    pv.x = __ldg((const unsigned short*)P.ldt + ch); pv.y = __ldg((const unsigned short*)P.ssm_D + ch); pv.z = __ldg((const unsigned short*)P.dskip + ch);
    pv.w = __ldcg(P.epoch + blockIdx.x);
  }
  if (tid == 256) {
    for (int i = 0; i < 4; i++) mbar_init(bars + 8 * i, 1);
    asm volatile("fence.mbarrier_init.release.cluster;" ::: "memory");
    TS(65);
    for (int i = 0; i < 4; i++) { mbar_expect(bars + 8 * (B_Q + i), 64 * PITCH); tma4(sm + RAWQ + i * 64 * PITCH, &mq, ch0, rank * 8 + 2 * i, bars + 8 * (B_Q + i)); }
    TS(66);
  } else if (tid == 288) {
#pragma unroll
    for (int i = 4; i < B_END; i++) mbar_init(bars + 8 * i, 1);
#pragma unroll
    for (int i = 4; i < B_END; i++) mbar_expect(bars + 8 * i, i == B_KV ? (256 + 288) * PITCH : i == B_KVT ? RMAX * 4096 : 4096);
    asm volatile("fence.mbarrier_init.release.cluster;" ::: "memory");
  } else if (tid == 320) {
    asm volatile("prefetch.tensormap [%0];" ::"l"(&mk) : "memory");
    asm volatile("prefetch.tensormap [%0];" ::"l"(&mv) : "memory");
    asm volatile("prefetch.tensormap [%0];" ::"l"(&mo8) : "memory");
    asm volatile("prefetch.tensormap [%0];" ::"l"(&mo16) : "memory");
  }
  __syncwarp();
  asm volatile("barrier.cluster.arrive.relaxed.aligned;" ::: "memory");
  const int wg = __shfl_sync(0xffffffffu, tid >> 7, 0), w = __shfl_sync(0xffffffffu, (tid >> 5) & 3, 0);
  const int g = lane >> 2, c = lane & 3;
  if (tid < 10) sts128(sm + UB + tid * UB_SZ + 4096, 0, 0, 0, 0);
  if (tid < 320) {
    const uint32_t pr = sm + PAR + (tid >> 6) * PAR_SZ;
    sts128(pr + (tid & 63) * 16, pv.x, pv.y, pv.z, pv.w);
    if (w & 1) {
      uint32_t mx = __vmaxu2(__vmaxu2(pv.x & 0x7fff7fffu, pv.y & 0x7fff7fffu), __vmaxu2(pv.z & 0x7fff7fffu, pv.w & 0x7fff7fffu));
      mx = __reduce_max_sync(0xffffffffu, max(mx & 0xffffu, mx >> 16));
      const uint32_t ex = min(max(mx >> 7, 1u), 253u);
      if (lane == 0) { sts32(pr + 1032, (254u - ex) << 23); sts32(pr + 1036, ex << 23); }
    }
  } else if (tid < 348) {
    const uint32_t sg = lane >= 8 ? 0x80008000u : 0u;
    sts128(sm + PAR2 + lane * 16, pv.x ^ sg, pv.y ^ sg, pv.z ^ sg, pv.w ^ sg);
  } else if (tid >= 352 && tid < 352 + RMAX) {
    sts32(sm + PAR + lane * PAR_SZ + 1024, __float_as_uint(rbf(expf(bf_lo(pv.x)))));
    sts32(sm + PAR + lane * PAR_SZ + 1028, pv.z << 16);
    sts32(sm + PAR3 + lane * 4, pv.y);
    if (lane == 0) { sts32(sm + PAR3 + 32, (pv.w + 1) & 255u); __stcg(P.epoch + blockIdx.x, pv.w + 1); }
  }
  __syncthreads();

  if (wg == 2) {
    asm volatile("setmaxnreg.dec.sync.aligned.u32 56;");
    TS(67);
    if (tid == 288) {
      tma4(sm + RAWK, &mk, ch0, rank * 8 - 1, bars + 8 * B_KV);
      tma4(sm + RAWV, &mv, ch0, rank * 8, bars + 8 * B_KV);
    }
    __syncwarp();
    const int lm = lane >> 3, lj = lane & 7;
    const int lt = 31 - (8 * (lj >> 1) + 2 * lm + (lj & 1));
    const uint32_t lrow = sm + (64 * w + (lt >> 3) + 4 * (lt & 7)) * PITCH;
    asm volatile("barrier.cluster.wait.aligned;" ::: "memory");
    const uint32_t rem = mapa(sm, g);
    const uint32_t xdst = rem + UB + 16 * (4 * (63 - (rank * 8 + 2 * w)) + c);
    TS(69);
    mbar_wait(bars + 8 * (B_Q + w));
    TS(70);
#pragma unroll
    for (int r = 0; r < RMAX; r++) {
#pragma unroll
      for (int b = 0; b < 2; b++) {
        uint32_t v[4];
        ldsm4t(v, lrow + RAWQ + b * 32 * PITCH + 16 * GO(r));
        st_async4(xdst + r * UB_SZ - 64 * b, v[0], v[1], v[2], v[3], rem + BARS + 8 * (B_U + r));
      }
    }
    TS(71);
    if (tid == 352) {
      for (int r = 1; r < RMAX; r++)
        asm volatile("cp.async.bulk.prefetch.L2.global [%0], %1;" ::"l"(P.ssm_k + (size_t)(ch0 + 8 * (r - ev) + rank) * S_LEN), "r"(4096) : "memory");
    }
    __syncwarp();
    const int t = tid - 256;
    const uint4* kp = (const uint4*)(P.ssm_k + (size_t)(ch0 + 32 * ev + rank) * S_LEN) + t;
    const int nxo = t < 127 ? 516 : 0;
    uint4 a0, a1; uint32_t n0, n1;
#define LOAD_TAPS() do { a0 = __ldg(kp); a1 = __ldg(kp + 128); n0 = __ldg((const uint32_t*)kp + 4); n1 = __ldg((const uint32_t*)kp + nxo); kp += S_LEN; } while (0)
    LOAD_TAPS();
    kp -= 5 * ev * S_LEN;
    const uint32_t tag = lds32(sm + PAR3 + 32);
    {
      uint32_t gw[RMAX];
#pragma unroll
      for (int r = 0; r < RMAX; r++) gw[r] = lds32(sm + PAR2 + 16 * r + 4 * c);
      float gs[4][4];
      const uint32_t qa = sm + RAWQ + (64 * w + (lane & 15)) * PITCH + 16 * (lane >> 4), qb = sm + RAWQ + (64 * w + lane) * PITCH + 64;
#pragma unroll
      for (int m = 0; m < 4; m++) {
        uint32_t v[4];
        gs[m][0] = gs[m][1] = gs[m][2] = gs[m][3] = 0.f;
        ldsm4(v, qa + 16 * m * PITCH); mma16(gs[m], v, gw[0], gw[1]);
        ldsm4(v, qa + 16 * m * PITCH + 32); mma16(gs[m], v, gw[2], gw[3]);
      }
#pragma unroll
      for (int m = 0; m < 2; m++) {
        uint32_t v[4];
        ldsm4(v, qb + 32 * m * PITCH); mma8(gs[2 * m], v[0], v[1], gw[4]); mma8(gs[2 * m + 1], v[2], v[3], gw[4]);
      }
      const float s0 = (c & 2) ? ((c & 1) ? gs[3][0] : gs[2][0]) : ((c & 1) ? gs[1][0] : gs[0][0]);
      const float s1 = (c & 2) ? ((c & 1) ? gs[3][2] : gs[2][2]) : ((c & 1) ? gs[1][2] : gs[0][2]);
      const int x = 2047 - (256 * rank + 64 * w + 32 * (c >> 1) + 8 * (g & 3) + 4 * (c & 1) + (g >> 2));
      __stcg(P.gate_part + cl * S_LEN + x, (__float_as_uint(s0) & ~255u) | tag);
      __stcg(P.gate_part + cl * S_LEN + x - 2, (__float_as_uint(s1) & ~255u) | tag);
    }
    TS(84);
    auto tables = [&](int r0, int r1) {
      bar_sync(NB_AUX, 128);
#pragma unroll 1
      for (int r = r0; r < r1; r++) {
        const uint32_t tb = sm + TAB + (5 + r) * TAB_SZ + 16 * t;
        if (t == 0) {
          a0.x = hadd(a0.x, lds32(sm + PAR3 + 4 * r));
          sts128(tb, 0, 0, 0, 0); sts128(tb + 4128, 0, 0, 0, a0.x << 16);
        }
        sts128(tb + 16, a0.x, a0.y, a0.z, a0.w);
        sts128(tb + 16 + 2048, a1.x, a1.y, a1.z, a1.w);
        const uint32_t o0 = prmt(a0.x, a0.y, 0x5432), o1 = prmt(a0.y, a0.z, 0x5432), o2 = prmt(a0.z, a0.w, 0x5432), o3 = prmt(a0.w, n0, 0x5432);
        const uint32_t o4 = prmt(a1.x, a1.y, 0x5432), o5 = prmt(a1.y, a1.z, 0x5432), o6 = prmt(a1.z, a1.w, 0x5432), o7 = prmt(a1.w, n1, 0x5432);
        if (r + 1 < RMAX) LOAD_TAPS();
        sts128(tb + 4144, o0, o1, o2, o3);
        sts128(tb + 4144 + 2048, o4, o5, o6, o7);
        bar_arrive(NB_TAB + r, 256);
      }
    };
    mbar_wait(bars + 8 * B_KV);
    TS(72);
    {
      const int lt2 = lt - 8;
      const uint32_t lrow2 = sm + (64 * w + ((lt2 >= 0) ? (lt2 >> 3) : 3 - 32) + 4 * (lt2 & 7)) * PITCH;
#pragma unroll 1
      for (int r = 0; r < RMAX; r++) {
        const int go = 16 * GO(r);
        const uint2 sw = lds64(sm + PAR2 + 128 + 4 * go + 8 * g);
        const uint32_t w0 = prmt(sw.x, 0, 0x1010), w1 = prmt(sw.x, 0, 0x3232), w2 = prmt(sw.y, 0, 0x1010), w3 = prmt(sw.y, 0, 0x3232);
#pragma unroll
        for (int b = 0; b < 2; b++) {
          uint32_t k4[4], k5, k6, v[4], o[4];
          ldsm4t(k4, lrow + RAWK + (b + 1) * 32 * PITCH + go);
          ldsm2t(k5, k6, lrow2 + RAWK + (b + 1) * 32 * PITCH + go);
          ldsm4t(v, lrow + RAWV + b * 32 * PITCH + go);
          const uint32_t R[6] = {k4[0], k4[1], k4[2], k4[3], k5, k6};
          uint32_t O[5];
#pragma unroll
          for (int i = 0; i < 5; i++) O[i] = prmt(R[i], R[i + 1], 0x5432);
#pragma unroll
          for (int i = 0; i < 4; i++) {
            uint32_t a = hmul(O[i + 1], w3);
            a = hadd(a, hmul(R[i + 1], w2));
            a = hadd(a, hmul(O[i], w1));
            a = hadd(a, hmul(R[i], w0));
            o[i] = hmul(a, v[i]);
          }
          st_async4(xdst + (RMAX + r) * UB_SZ - 64 * b, o[0], o[1], o[2], o[3], rem + BARS + 8 * B_KVT);
        }
      }
    }
    TS(73);
    tables(0, RMAX);
    TS(74);
    {
      const int x0 = 256 * (7 - rank) + 2 * t;
      float s0, s1;
      uint32_t bad = 1;
#pragma unroll 1
      for (int it = 0; it < (1 << 20) && bad; it++) {
        s0 = 0.f; s1 = 0.f; bad = 0;
        uint2 p[NCL];
#pragma unroll
        for (int k = 0; k < NCL; k++) asm volatile("ld.relaxed.gpu.global.v2.u32 {%0,%1}, [%2];" : "=r"(p[k].x), "=r"(p[k].y) : "l"(P.gate_part + k * S_LEN + x0) : "memory");
#pragma unroll
        for (int k = 0; k < NCL; k++) { bad |= (p[k].x ^ tag) | (p[k].y ^ tag); s0 += __uint_as_float(p[k].x); s1 += __uint_as_float(p[k].y); }
        bad &= 255u;
      }
      if (bad) __trap();
      s0 = rbf(s0); s1 = rbf(s1);
      const uint32_t gg = pack_bf(__fdividef(-1.f, 1.f + __expf(-s0)), __fdividef(-1.f, 1.f + __expf(-s1)));
#pragma unroll
      for (int k = 0; k < CLS; k++) { const uint32_t rb = mapa(sm, k); st_async1(rb + GBUF + 2 * x0, gg, rb + BARS + 8 * B_G); }
    }
    TS(75);
    TS(85);
    const uint32_t ra = sm + RECV + lj * RECV_PITCH + (8 * w + lm) * 16;
    const int row = 255 - 64 * w - lane;
#pragma unroll 1
    for (int r = 0; r < RMAX; r++) {
      const uint32_t ot = sm + OUTB + (r == 0 ? 0 : r < 3 ? 4096 : SCR_SZ);
      const uint32_t oa = r == 0 ? ot + 16 * row : ot + 32 * row + ((((row >> 2) ^ r ^ 1) & 1) << 4);
      mbar_wait(bars + 8 * (B_O + r));
      TS(76 + r);
      uint32_t v0[4], v1[4];
      ldsm4t(v0, ra + r * RECV_SZ);
      ldsm4t(v1, ra + r * RECV_SZ + 64);
      stsm4(oa, v0);
      stsm4(oa - (r == 0 ? 512 : 1024), v1);
      if (!(r & 1)) {
        fence_async();
        __syncwarp();
        if (lane == 0) {
          if (r == 0) tma_store(&mo8, ot + 1024 * (3 - w), ch0 + 32 * ev, 256 * rank + 64 * (3 - w));
          else tma_store(&mo16, ot + 2048 * (3 - w), ch0 + 8 * (r - 1 - ev), 256 * rank + 64 * (3 - w));
        }
      }
    }
    if (lane == 0) { asm volatile("cp.async.bulk.commit_group;" ::: "memory"); asm volatile("cp.async.bulk.wait_group.read 0;" ::: "memory"); }
    TS(81); TG(83); TS_DUMP();
  } else {
    asm volatile("setmaxnreg.inc.sync.aligned.u32 224;");
    const int t = 32 * w + lane;
    if (wg == 1) bar_arrive(NB_TURN, 256);
    {
      const int odd = t & 1;
      const uint32_t sAA = odd ? 0x3232 : 0x1010, sBB = odd ? 0x5454 : 0x3232, sE2 = odd ? 0x5454 : 0x3210, sO1 = odd ? 0x5432 : 0x1010;
      KSetup ks = ksetup(sm + PAR + wg * PAR_SZ, t);
      if (wg == 0) bar_sync(NB_TAB + 5, 256);
#pragma unroll 1
      for (int k = wg; k < 4 + wg; k += (k == 3 ? 1 : 2)) {
        uint32_t scr = sm + SCR + wg * SCR_SZ;
        asm volatile("" : "+r"(scr));
        scr = __shfl_sync(0xffffffffu, scr, 0);
        const uint32_t cmp = scr + CMP;
        TS(wg * 32 + 25);
        const uint32_t so = scr + ((t >> 4) & 3) * 512 + (t & 15) * 16;
        kstage(ks, so + (w >> 1) * 8192, so + 16384 + (w >> 1) * 6144);
        TS(wg * 32 + 27);
        fence_async();
        if (k == 1) bar_arrive(NB_TAB + 5, 256);
        bar_sync(NB_WG + wg, 128);
        float d[24];
        wg_fence();
        kmma<0>(d, (uint64_t)((scr & 0x3FFFF) >> 4) | ((uint64_t)8 << 16) | ((uint64_t)128 << 32));
        wg_commit();
        TS(wg * 32 + 28);
        const uint4 sc4 = lds128(sm + PAR + k * PAR_SZ + 1024);
        if (k < 2 + 2 * wg) ks = ksetup(sm + PAR + (k + (k == 3 ? 1 : 2)) * PAR_SZ, t);
        TS(wg * 32 + 26);
        wg_wait<0>();
        TS(wg * 32 + 29);
        {
          const float sc = 2.f * __uint_as_float(sc4.x) * __uint_as_float(sc4.w);
          const int j = 16 * (w & 1) + g;
          const float skip = t == 0 ? __uint_as_float(sc4.y) : 0.f;
          const uint32_t cb = cmp + (w >> 1) * CMP_H;
          const uint32_t a1 = cb + 4 * (c < 2 ? 128 + 2 * j + c : 128 + 32 * c + j);
          if (w < 2) kcompact(d, sc, skip, cb + 4 * (4 * j + c), a1, a1 + (c < 2 ? 64 : 32), cb + 2 * (512 + 64 * c + j), c < 2, (t & 63) == 2);
          else kcompact(d + 12, sc, skip, cb + 4 * (4 * j + c), a1, a1 + (c < 2 ? 64 : 32), cb + 2 * (512 + 64 * c + j), c < 2, (t & 63) == 2);
        }
        bar_sync(NB_WG + wg, 128);
        const uint32_t tb = sm + TAB + k * TAB_SZ + 16 * t;
        const uint32_t u0 = cmp32(cmp + 1024 + 4 * (t >> 1)), u1 = cmp32(cmp + 1024 + 4 * ((t + 1) >> 1));
        if (w == 0) {
          uint4 q = lds128(cmp + 16 * lane);
          const uint4 q2 = lds128(cmp + CMP_H + 16 * lane);
          const uint32_t nx = cmp32(cmp + 16 * lane + 16);
          q.x = hadd(q.x, q2.x); q.y = hadd(q.y, q2.y); q.z = hadd(q.z, q2.z); q.w = hadd(q.w, q2.w);
          sts128(tb + 16, q.x, q.y, q.z, q.w);
          sts128(tb + 4144, prmt(q.x, q.y, 0x5432), prmt(q.y, q.z, 0x5432), prmt(q.z, q.w, 0x5432), prmt(q.w, nx, 0x5432));
          if (lane == 0) { sts128(tb, 0, 0, 0, 0); sts128(tb + 4128, 0, 0, 0, q.x << 16); }
        } else if (w == 1) {
          uint2 q = lds64(cmp + 512 + 8 * lane);
          const uint2 q2 = lds64(cmp + CMP_H + 512 + 8 * lane);
          const uint32_t nx = cmp32(cmp + 520 + 8 * lane);
          q.x = hadd(q.x, q2.x); q.y = hadd(q.y, q2.y);
          sts128(tb + 16, prmt(q.x, 0, 0x1010), prmt(q.x, q.y, 0x5432), prmt(q.y, 0, 0x1010), prmt(q.y, nx, 0x5432));
          sts128(tb + 4144, q.x, prmt(q.y, q.x, 0x1010), q.y, prmt(nx, 0, 0x1010));
        } else {
          const uint32_t q = cmp32(cmp + 512 + 4 * t), nx = cmp32(cmp + 516 + 4 * t);
          sts128(tb + 16, prmt(q, 0, 0x1010), q, prmt(q, 0, 0x3232), prmt(nx, 0, 0x1010));
          sts128(tb + 4144, prmt(q, nx, 0x1010), prmt(q, nx, 0x3232), prmt(q, nx, 0x5432), prmt(nx, q, 0x1010));
        }
        const uint32_t aa = prmt(u0, u1, sAA), bb = prmt(u0, u1, sBB);
        sts128(tb + 16 + 2048, aa, aa, prmt(u0, u1, sE2), bb);
        sts128(tb + 4144 + 2048, aa, prmt(u0, u1, sO1), bb, bb);
        TS(wg * 32 + 30);
        if (k < 4) TS(wg * 32 + 1 + (k >> 1));
      }
    }
    if (lane < 8) sts128(sm + SCR + wg * SCR_SZ + w * PLANE + 4096 + lane * 16, 0, 0, 0, 0);
    const int s0 = 2 * c - g + 16 * w;
    const uint32_t ta = sm + TAB + ((g & 1) ? 4144 + 2 * (s0 - 1) : 16 + 2 * s0);
    uint32_t a[64];
#pragma unroll
    for (int i = 0; i < 64; i++) a[i] = lds32(ta + wg * TAB_SZ + TAPOFF(i));
    asm volatile("barrier.cluster.wait.aligned;" ::: "memory");
    mbar_wait(bars + 8 * (B_U + wg)); mbar_wait(bars + 8 * (B_U + 2 + wg)); mbar_wait(bars + 8 * (B_U + 4));
    fence_async();
    int u = wg;
#pragma unroll 1
    for (; u < RMAX; u += 2) conv_unit<true>(a, sm, u, wg, w, lane, rank, ta);
#pragma unroll 1
    for (; u < 2 * RMAX; u += 2) conv_unit<false>(a, sm, u, wg, w, lane, rank, ta);
  }
}

typedef CUresult (*EncodeFn)(CUtensorMap*, CUtensorMapDataType, cuuint32_t, void*, const cuuint64_t*, const cuuint64_t*, const cuuint32_t*, const cuuint32_t*,
                             CUtensorMapInterleave, CUtensorMapSwizzle, CUtensorMapL2promotion, CUtensorMapFloatOOBfill);

static void make_map(EncodeFn fn, CUtensorMap* m, void* p, int hi) {
  cuuint64_t dims[4] = {(cuuint64_t)D_CH, 4, 8, S_LEN / 32};
  cuuint64_t strides[3] = {8ull * D_CH * 2, (cuuint64_t)D_CH * 2, 32ull * D_CH * 2};
  cuuint32_t box[4] = {RMAX * 8, 4, 8, (cuuint32_t)hi};
  cuuint32_t es[4] = {1, 1, 1, 1};
  fn(m, CU_TENSOR_MAP_DATA_TYPE_BFLOAT16, 4, p, dims, strides, box, es, CU_TENSOR_MAP_INTERLEAVE_NONE, CU_TENSOR_MAP_SWIZZLE_NONE,
     CU_TENSOR_MAP_L2_PROMOTION_L2_128B, CU_TENSOR_MAP_FLOAT_OOB_FILL_NONE);
}

static void make_out_map(EncodeFn fn, CUtensorMap* m, void* p, int nch) {
  cuuint64_t dims[2] = {(cuuint64_t)D_CH, (cuuint64_t)S_LEN};
  cuuint64_t strides[1] = {(cuuint64_t)D_CH * 2};
  cuuint32_t box[2] = {(cuuint32_t)nch, 64};
  cuuint32_t es[2] = {1, 1};
  fn(m, CU_TENSOR_MAP_DATA_TYPE_BFLOAT16, 2, p, dims, strides, box, es, CU_TENSOR_MAP_INTERLEAVE_NONE,
     nch == 16 ? CU_TENSOR_MAP_SWIZZLE_32B : CU_TENSOR_MAP_SWIZZLE_NONE, CU_TENSOR_MAP_L2_PROMOTION_NONE, CU_TENSOR_MAP_FLOAT_OOB_FILL_NONE);
}

extern "C" void kernel_launch(void* const* d_in, const int* in_sizes, int n_in, void* d_out, int out_size) {
  static EncodeFn fn = nullptr;
  static void *gp = nullptr, *ep = nullptr;
  if (!fn) {
    void* p = nullptr;
    cudaDriverEntryPointQueryResult qr;
    cudaGetDriverEntryPoint("cuTensorMapEncodeTiled", &p, cudaEnableDefault, &qr);
    fn = (EncodeFn)p;
    cudaGetSymbolAddress(&gp, g_gate_part);
    cudaGetSymbolAddress(&ep, g_epoch);
    cudaFuncSetAttribute(fused_kernel, cudaFuncAttributeMaxDynamicSharedMemorySize, SMEM_TOTAL);
  }
  CUtensorMap mq, mk, mv, mo8, mo16;
  make_out_map(fn, &mo8, d_out, 8);
  make_out_map(fn, &mo16, d_out, 16);
  make_map(fn, &mq, d_in[0], 2);
  make_map(fn, &mk, d_in[1], 9);
  make_map(fn, &mv, d_in[2], 8);
  Params P;
  P.shift_k = (const bf16*)d_in[3]; P.ssm_k = (const bf16*)d_in[4]; P.ssm_D = (const bf16*)d_in[5];
  for (int i = 0; i < 4; i++) P.s4[i] = (const bf16*)d_in[7 + i];
  P.ldt = (const bf16*)d_in[11]; P.dskip = (const bf16*)d_in[12]; P.gate_w = (const bf16*)d_in[13];
  P.gate_part = (unsigned int*)gp; P.epoch = (unsigned int*)ep;
  cudaLaunchConfig_t cfg = {};
  cfg.gridDim = dim3(NCL * CLS); cfg.blockDim = dim3(384); cfg.dynamicSmemBytes = SMEM_TOTAL; cfg.stream = cudaStreamPerThread;
  cudaLaunchAttribute at[1];
  at[0].id = cudaLaunchAttributeClusterDimension; at[0].val.clusterDim.x = CLS; at[0].val.clusterDim.y = 1; at[0].val.clusterDim.z = 1;
  cfg.attrs = at; cfg.numAttrs = 1;
  cudaLaunchKernelEx(&cfg, fused_kernel, mq, mk, mv, mo8, mo16, P);
}
```

```cpp
#include <cuda_runtime.h>
#include <cuda_bf16.h>
#include <cuda_fp16.h>
#include <cuda.h>
#include <stdint.h>

typedef __nv_bfloat16 bf16;
#define FUSEKV 1
#define TL0 0x9530u
#define TL1 0x641u
#define TL2 0x72u
#define TL3 0x8u
#define KL0 0x0u
#define KL1 0x1u
#define KL2 0x243u
#define OUTMAP 0x3210
#define SECOND 1
#define STAG 1

constexpr int S_LEN = 2048, D_CH = 576, NST = 128;
constexpr int NCL = 15, CLS = 8, RMAX = 5;
constexpr int PITCH = RMAX * 16;

constexpr int SIG = 0;
constexpr int GBUF = SIG + 10 * 4096;
constexpr int B2 = GBUF + 4096;
constexpr int SCR = B2 + 2048;
constexpr int SCR_SZ = 31744;
constexpr int CMP = 28672, CMP_H = 1312;
constexpr int KT = SCR + 20480;
constexpr int RAWQ = SCR + 3 * SCR_SZ;
constexpr int TAPA = RAWQ;
constexpr int RAWK = KT + 3 * SCR_SZ + 4096;
constexpr int BARS = RAWK + 288 * PITCH;
constexpr int PAR2 = BARS + 256;
constexpr int PAR3 = PAR2 + 448;
constexpr int MX = PAR2 + 512;
constexpr int PROFB = MX + 128;
constexpr int RAWV = KT + 4 * SCR_SZ + 4096;
constexpr int PAR = RAWV + 256 * PITCH;
constexpr int PAR_SZ = 1040;
constexpr int SMEM_TOTAL = PAR + RMAX * PAR_SZ;
constexpr int OUTB = RAWV;
constexpr int RECV = RAWK;
constexpr int RECV_SZ = 4256, RECV_PITCH = 528;
static_assert(SMEM_TOTAL <= 232448 && SCR % 512 == 0 && SCR_SZ % 512 == 0 && RAWK % 128 == 0 && RAWV % 256 == 0 && KT % 512 == 0, "smem");
static_assert(RMAX * RECV_SZ <= 288 * PITCH && CMP + 2 * CMP_H <= SCR_SZ && RAWQ + 256 * PITCH <= KT + 3 * SCR_SZ && PROFB + 512 <= KT + 4 * SCR_SZ, "smem");
enum { B_Q = 0, B_KV = 2, B_T = 3, B_U = 4, B_G = 14, B_O = 15, B_Y = 20, B_END = 25 };
enum { NB_WG = 1, NB_STAG = 5 };

__device__ __align__(128) const uint32_t g_dft[4096] = {
0x3f7f3f80,0xbd94bcbc,0x3f653f6a,0xbee5becf,0x3f7c3f7e,0xbe2ebdf8,0x3f583f5f,0xbf09befc,0x3f773f7a,0xbe88be5f,0x3f4a3f52,0xbf1dbf13,
0x3f6f3f73,0xbeb8bea0,0x3f3a3f42,0xbf30bf27,0x3f7a3f7f,0xbe5cbd8d,0x3e343ea3,0xbf7cbf73,0x3f5f3f6f,0xbefabeb6,0xbdf13cef,0xbf7ebf80,
0x3f313f4b,0xbf39bf1d,0xbecdbe86,0xbf6bbf77,0x3ee83f14,0xbf64bf51,0xbf26bf08,0xbf43bf59,0x3f703f7e,0xbeb5bdeb,0xbf2fbef9,0xbf3bbf60,
0x3f293f52,0xbf41bf12,0xbf72bf57,0xbea4bf0b,0x3e683eea,0xbf79bf64,0xbf7dbf7f,0x3e27bda6,0xbe85bc8a,0xbf77bf80,0xbf4bbf6b,0x3f1c3ecc,
0x3f603f7d,0xbef8be24,0xbf7ebf79,0x3de5be6b,0x3ebd3f29,0xbf6ebf40,0xbf33bf66,0x3f383ee1,0xbe9b3d10,0xbf74bf80,0xbdadbed4,0x3f7f3f69,
0xbf57bf1b,0xbf0bbf4b,0x3f113e83,0x3f533f77,0x3f4c3f7b,0xbf1bbe53,0xbf01bf53,0x3f5d3f11,0x3d1d3eec,0xbf80bf63,0x3eb2bdb3,0x3f703f7f,
0xbf40bec9,0xbf2abf6b,0x3f723f37,0x3ea73f33,0xbf7dbf76,0x3e21be8f,0x3f5a3f7e,0xbf06bddf,0x3f343f78,0xbf36be80,0x3ec8be0e,0x3f6c3f7e,
0xbe983e71,0xbf74bf79,0x3f7f3f4f,0x3db93f17,0xbf7bbf3f,0xbe40bf2a,0x3f0d3f67,0xbf56bede,0xbf21bf70,0x3f473eb0,0xbef53d2a,0xbf61bf80,
0x3f183f75,0xbf4ebe97,0x3f793f23,0x3e743f45,0xbf19bb97,0xbf4dbf80,0x3f033f6c,0xbf5cbec6,0xbf71bf75,0x3eafbe92,0xbf2dbdd2,0xbf3dbf7f,
0x3d5cbf0d,0x3f803f56,0xbf67bf7b,0x3eddbe43,0x3ef13f71,0xbf62bead,0x3f463f80,0xbf233d43,0xbf55be7a,0xbf0ebf78,0xbf0f3e15,0xbf55bf7d,
0xbf22bf7d,0x3f463e18,0xbf62bf78,0x3ef2be77,0x3f353d4f,0x3f353f80,0x3ec5beac,0x3f6c3f71,0x3ead3f6d,0xbf71bec3,0xbd433f35,0xbf80bf35,
0xbf78bef1,0xbe7abf62,0xbf7dbf46,0x3e15bf23,0xbe18bf55,0x3f7d3f0e,0x3e77bf0f,0x3f783f55,0x3f803f22,0x3d4f3f46,0x3f713f62,0xbeac3ef2,
0x3e4c3f68,0xbf7bbed9,0xbf54bd36,0xbf0fbf80,0xbf7fbf2b,0x3dbfbf3e,0xbe97bf71,0x3f753eaa,0x3ec2bf05,0x3f6d3f5b,0x3f803f18,0x3b973f4e,
0x3f473f78,0xbf213e7d,0xbe923f19,0xbf75bf4d,0x3d683f63,0xbf80beee,0xbf72bf45,0x3ea9bf24,0xbf68bf54,0x3ed7bf10,0x3f3cbe4f,0x3f2d3f7b,
0x3f4cbdd8,0x3f1a3f7f,0x3e803f76,0xbf78be91,0x3e1e3f6d,0xbf7dbec0,0xbf79bf34,0x3e71bf36,0xbdb33f5d,0xbf7fbf01,0xbe9abf7e,0x3f743e0b,
0xbf37bf70,0x3f33beb2,0x3f6e3f3c,0xbebf3f2e,0x3f7e3ea7,0x3ddf3f72,0xbf603d75,0xbef6bf80,0xbf0c3f06,0xbf56bf5a,0x3e3dbf4f,0x3f7c3f16,
0xbe6b3f57,0xbf79bf0b,0x3f16bf11,0x3f503f53,0xbee1bf7e,0x3f66bde5,0x3d813f76,0xbf7fbe8e,0x3f693f33,0xbed43f38,0xbf2fbf6b,0x3f3bbeca,
0xbf77bdad,0xbe83bf7f,0x3f7e3eeb,0xbe083f63,0xbebc3f50,0xbf6ebf15,0x3f803e68,0x3c8a3f79,0xbdebbf7e,0x3f7e3e05,0xbf603e85,0xbef9bf77,
0x3f123f70,0xbf523eb5,0x3f0bbf2f,0x3f573f3b,0xbf64bf29,0x3eeabf41,0xbda63f72,0xbf7fbea4,0xbefe3f49,0xbf5ebf1e,0x3f1d3f5f,0xbf4b3efa,
0x3e65bf6e,0x3f7a3eba,0xbf51bf31,0x3f14bf39,0x3d8d3f7f,0xbf7fbda0,0x3f733ee8,0xbea33f64,0xbeb6bf7a,0x3f6fbe5c,0xbf80be34,0x3cefbf7c,
0xbf1e3f42,0xbf4abf28,0xbe893f73,0xbf77bea1,0x3f09bf51,0x3f583f14,0x3e31bf7a,0x3f7c3e62,0xbee73f5f,0xbf64befd,0xbd9a3f7e,0xbf7fbdfe,
0x3eb9bf6a,0x3f6f3ed0,0xbcbcbf80,0x3f803cd6,0xbf393f3a,0xbf31bf30,0xbf6f3ed0,0xbeb9bf6a,0x3f4abf28,0x3f1e3f42,0x3f77bea1,0x3e893f73,
0xbf583f14,0xbf09bf51,0xbf7c3e62,0xbe31bf7a,0x3f64befd,0x3ee73f5f,0x3f7fbdfe,0x3d9a3f7e,0xbf513f31,0xbf14bf39,0xbf59becd,0x3f08bf6b,
0x3f73bee8,0x3ea33f64,0x3f283f26,0xbf413f43,0xbf803e34,0xbcefbf7c,0xbed2bf58,0x3f6abf0a,0x3f773df1,0xbe863f7e,0x3e023f76,0xbf7e3e8b,
0xbf643f29,0xbeeabf41,0xbda6bf72,0x3f7fbea4,0x3f80be68,0xbc8a3f79,0xbecc3f7d,0xbf6bbe27,0xbf60be85,0x3ef9bf77,0x3f49bf4b,0x3f1f3f1c,
0x3f0b3f2f,0xbf573f3b,0xbf7c3ed3,0xbe37bf69,0xbf723f20,0xbea6bf48,0x3f40bf60,0x3f293ef8,0x3f703c62,0xbeb33f80,0xbf803ebd,0xbd10bf6e,
0xbf01bf25,0x3f5dbf44,0x3f4b3e9b,0xbf1b3f74,0xbe243f7c,0xbf7d3e3a,0xbe6bbf57,0x3f79bf0b,0xbf7c3f16,0xbe3dbf4f,0x3f7bbe6e,0xbe533f79,
0x3f443e82,0xbf253f78,0xbeecbf1b,0x3f63bf4c,0x3c30bf69,0x3f80bed6,0xbec93f80,0xbf6b3d1d,0xbf483f66,0xbf20bee0,0x3f76bf2a,0x3e8f3f40,
0xbf803f0d,0xbd2abf56,0x3ed73f10,0xbf683f54,0x3f023ef5,0xbf5d3f61,0x3f1abf7f,0x3f4c3dd8,0x3f05bf80,0x3f5b3bfb,0xbf7d3ec0,0x3e1ebf6d,
0xbf803eee,0x3d68bf63,0x3ea93f24,0xbf723f45,0xbf7f3f03,0x3dd2bf5c,0xbef33f7d,0xbf613e12,0x3e433f2d,0xbf7b3f3d,0x3f7bbed9,0xbe4c3f68,
0x3f62bf67,0x3eef3edd,0xbdbfbf3e,0x3f7fbf2b,0xbf34be1b,0x3f36bf7d,0xbf6d3f5b,0xbec2bf05,0xbf783ef1,0x3e7abf62,0xbf7d3f46,0xbe15bf23,
0xbe183f55,0xbf7d3f0e,0x3e773f0f,0xbf783f55,0x3f80bf22,0xbd4f3f46,0x3f71bf62,0x3eac3ef2,0xbd43bf35,0x3f80bf35,0xbedabec5,0x3f68bf6c,
0xbf6d3edc,0x3ec3bf67,0xbf353d4f,0x3f35bf80,0xbef13f71,0xbf623ead,0xbf463f80,0xbf23bd43,0x3f55be7a,0xbf0e3f78,0x3f0f3e15,0xbf553f7d,
0x3f22bf7d,0x3f46be18,0x3f62bf78,0x3ef23e77,0xbf5c3ec6,0x3f03bf6c,0x3e12bf34,0x3f7dbf36,0xbf3d3f7f,0xbf2d3dd2,0xbf683ef3,0x3ed9bf61,
0x3edd3e43,0xbf673f7b,0xbf2b3f7b,0xbf3e3e4c,0x3f7dbf62,0x3e1b3eef,0x3f053dbf,0xbf5b3f7f,0xbf473eb0,0x3f21bf70,0x3f61bf80,0x3ef53d2a,
0xbf6c3f7e,0xbec8be0e,0xbbfbbf02,0x3f80bf5d,0xbdb93f17,0xbf7f3f4f,0xbf633f05,0x3eeebf5b,0x3f56bede,0xbf0d3f67,0xbf543f80,0xbf103d68,
0xbf2e3e9a,0x3f3cbf74,0x3f69bf25,0xbed63f44,0xbf803f6e,0xbd75bebf,0x3f66bf80,0x3ee0bc30,0xbf163f60,0xbf4f3ef6,0x3e6ebf20,0x3f79bf48,
0x3e823e3d,0xbf783f7c,0xbf1b3e53,0x3f4cbf7b,0xbf113e83,0x3f53bf77,0x3e563e08,0xbf7a3f7e,0xbf763f50,0x3e8ebf16,0x3f48bf07,0xbf203f5a,
0xbf6b3f7f,0xbeca3d81,0x3f80bf72,0x3c623ea6,0xbeeb3f3b,0xbf633f2f,0x3f44bf70,0x3f25beb3,0xbee33e59,0x3f66bf7a,0xbf293f52,0xbf413f12,
0xbf503f26,0x3f15bf43,0xbe683eea,0xbf793f64,0xbf7e3f6e,0x3e05bebc,0x3e85bc8a,0xbf773f80,0xbf703f7e,0xbeb53deb,0x3f2fbef9,0xbf3b3f60,
0xbe9e3e2a,0x3f73bf7c,0xbf7f3f7a,0x3da0be65,0xbf123ee4,0x3f52bf65,0xbf7a3f7f,0xbe5c3d8d,0xbf493f30,0x3f1ebf3a,0xbf5f3f6f,0xbefa3eb6,
0xbf6e3f5e,0x3ebabefe,0xbf313f4b,0xbf393f1d,0xbe2e3df8,0x3f7cbf7e,0xbf093efc,0x3f58bf5f,0xbe883e5f,0x3f77bf7a,0xbf1d3f13,0x3f4abf52,
0xbeb83ea0,0x3f6fbf73,0xbf303f27,0x3f3abf42,0xbee53ecf,0x3f65bf6a,0xbf423f39,0x3f28bf31,0x3f283f31,0xbf42bf39,0x3ea13eb9,0xbf73bf6f,
0x3f143f1e,0xbf51bf4a,0x3e623e89,0xbf7abf77,0x3efd3f09,0xbf5fbf58,0x3dfe3e31,0xbf7ebf7c,0x3ed03ee7,0xbf6abf64,0x3cd63d9a,0xbf80bf7f,
0xbf58bf41,0xbf0abf28,0xbf52bf65,0x3f123ee4,0xbf76bf6a,0xbe8bbed2,0xbf1ebf3a,0x3f493f30,0xbf80bf7e,0x3ca3be02,0xbebabefe,0x3f6e3f5e,
0xbf73bf7c,0x3e9e3e2a,0xbda0be65,0x3f7f3f7a,0xbed3bf1f,0x3f693f49,0x3f803f76,0x3d043e8c,0x3d87be37,0x3f7f3f7c,0x3f663f7a,0xbee3be59,
0x3f073e9d,0x3f593f74,0x3f153f43,0xbf50bf26,0x3f5e3f38,0x3f003f32,0x3e053ebc,0xbf7ebf6e,0x3f763f50,0x3e8e3f16,0xbf48bf07,0xbf20bf5a,
0x3f6b3f7f,0xbecabd81,0xbf80bf72,0x3c62bea6,0x3eeb3f3b,0xbf63bf2f,0xbf44bf70,0x3f253eb3,0xbe563e08,0xbf7abf7e,0xbe3abf01,0x3f7c3f5d,
0x3e0b3f0c,0xbf7ebf56,0x3e82be3d,0x3f783f7c,0xbf2ebe9a,0xbf3cbf74,0x3f693f25,0x3ed63f44,0xbf80bf6e,0x3d75bebf,0x3f663f80,0xbee0bc30,
0xbf16bf60,0x3f4f3ef6,0x3e6e3f20,0xbf79bf48,0xbf80bf5d,0x3bfbbf02,0x3ec03f4c,0xbf6dbf1a,0xbeeebf5b,0x3f633f05,0xbf24be1e,0xbf45bf7d,
0x3f103d68,0x3f543f80,0xbf7bbf72,0x3e4fbea9,0x3f7f3f68,0xbdd83ed7,0xbe91bf3c,0x3f763f2d,0x3e1bbeef,0x3f7d3f62,0xbf5bbf7f,0x3f05bdbf,
0x3f7d3f36,0x3e123f34,0x3e7dbec2,0x3f783f6d,0x3ed93f61,0xbf68bef3,0x3f803f47,0x3d363f21,0xbf3ebe4c,0xbf2bbf7b,0x3eaa3f54,0xbf71bf0f,
0x3f753f68,0xbe953eda,0x3f7f3f2c,0x3dc63f3d,0xbe493f03,0xbf7bbf5c,0x3e463f4d,0xbf7bbf19,0xbf7fbf4e,0x3dccbf18,0xbf75bf04,0xbe94bf5b,
0x3ac9bf2c,0x3f803f3e,0xbec3bf67,0x3f6d3edc,0xbeda3ec5,0xbf68bf6c,0xbf3d3ac9,0xbf2cbf80,0xbf5cbf75,0x3f03be95,0xbf19bf7f,0x3f4d3dc6,
0x3f18be49,0x3f4e3f7b,0x3f5b3e46,0x3f043f7b,0x3f3e3f7f,0xbf2c3dcc,0x3edc3f75,0xbf67be94,0xbf56bf71,0x3f0dbeaf,0x3e43bf2d,0x3f7b3f3d,
0x3f45bd5c,0x3f233f80,0x3f623f67,0xbeef3edd,0x3ec63f79,0xbf6cbe74,0xbf343e1b,0xbf36bf7d,0xbf7fbf03,0xbdd2bf5c,0xbef3bf7d,0x3f613e12,
0x3f2abe98,0x3f3f3f74,0x3ede3f7f,0xbf67bdb9,0x3eb03f7b,0xbf70be40,0xbf80bf0d,0x3d2abf56,0xbf7ebf21,0x3e0ebf47,0x3f02bef5,0x3f5d3f61,
0x3f17bec8,0x3f4f3f6c,0x3f053f80,0xbf5b3bfb,0x3f253f78,0xbf443e82,0xbf63bf4c,0x3eecbf1b,0xbf80bed6,0xbc30bf69,0x3f6b3d1d,0x3ec93f80,
0x3f20bee0,0x3f483f66,0xbe8f3f40,0xbf76bf2a,0x3e533f79,0xbf7bbe6e,0xbf11bf7d,0x3f53be21,0xbf5a3e56,0xbf07bf7a,0x3f7d3e3a,0x3e243f7c,
0x3ea6bf48,0x3f723f20,0xbf293ef8,0xbf40bf60,0x3eb33f80,0xbf703c62,0x3d10bf6e,0x3f803ebd,0xbf5dbf44,0x3f01bf25,0x3f1b3f74,0xbf4b3e9b,
0xbeccbf7d,0x3f6bbe27,0xbf323f07,0xbf38bf59,0x3f493f4b,0xbf1f3f1c,0x3e8cbf5e,0x3f763f00,0xbf7cbed3,0x3e37bf69,0x3e593f80,0xbf7abd04,
0x3f74bd87,0x3e9d3f7f,0xbf26bf66,0x3f43bee3,0x3f77bdf1,0x3e863f7e,0x3e02bf76,0x3f7e3e8b,0xbf593ecd,0xbf08bf6b,0x3e2a3f80,0xbf7c3ca3,
0x3f28bf26,0x3f413f43,0xbee4bf73,0x3f65be9e,0xbed23f58,0xbf6abf0a,0x3f303f52,0xbf3a3f12,0x3df83f7f,0xbf7e3d94,0x3efc3f65,0xbf5f3ee5,
0xbe5fbf7c,0x3f7abe2e,0xbf13bf58,0x3f52bf09,0x3ea03f77,0xbf733e88,0x3f273f4a,0xbf423f1d,0xbecfbf6f,0x3f6abeb8,0xbf39bf3a,0x3f31bf30,
0xbf803cd6,0x3cbcbf80,0xbf6abeb8,0x3ecfbf6f,0x3f7e3d94,0xbdf83f7f,0x3f5f3ee5,0xbefc3f65,0xbf7abe2e,0x3e5fbf7c,0xbf52bf09,0x3f13bf58,
0x3f733e88,0xbea03f77,0x3f423f1d,0xbf273f4a,0x3e2abf80,0x3f7c3ca3,0x3f7abeba,0x3e653f6e,0xbee43f73,0xbf65be9e,0xbf7f3da0,0x3d8dbf7f,
0x3f30bf52,0x3f3a3f12,0x3f6f3e5c,0xbeb63f7a,0xbf5e3f1e,0xbefebf49,0xbf4bbefa,0x3f1dbf5f,0x3f743d87,0xbe9d3f7f,0xbf263f66,0xbf43bee3,
0xbf32bf07,0x3f38bf59,0x3f6ebf15,0x3ebc3f50,0x3e8c3f5e,0xbf763f00,0xbf7e3e05,0x3debbf7e,0x3e59bf80,0x3f7abd04,0x3f523eb5,0xbf123f70,
0xbee13f7e,0xbf66bde5,0x3d81bf76,0x3f7fbe8e,0x3f69bf33,0x3ed43f38,0xbf2f3f6b,0xbf3bbeca,0xbf773dad,0x3e83bf7f,0x3f7ebeeb,0x3e083f63,
0x3f163f11,0xbf503f53,0xbf5abe56,0x3f07bf7a,0xbf53be21,0x3f11bf7d,0x3f0c3f06,0xbf563f5a,0x3db33f5d,0xbf7f3f01,0x3e9abf7e,0x3f74be0b,
0x3f37bf70,0x3f333eb2,0xbf6e3f3c,0xbebfbf2e,0xbf7e3ea7,0x3ddfbf72,0x3f603d75,0xbef63f80,0x3f2dbf7b,0x3f3c3e4f,0xbf703e40,0x3eb0bf7b,
0xbf783e91,0x3e80bf76,0x3e0e3f47,0xbf7e3f21,0x3e713f36,0xbf793f34,0x3f4fbf6c,0x3f173ec8,0x3f3fbf74,0x3f2a3e98,0xbf673db9,0x3edebf7f,
0x3f213e7d,0xbf473f78,0x3f75bf4d,0x3e923f19,0x3f0fbf80,0x3f54bd36,0xbf0dbeaf,0x3f56bf71,0xbf753eaa,0x3e97bf71,0xbf233f80,0xbf45bd5c,
0xbb973f4e,0xbf803f18,0x3f6cbe74,0xbec63f79,0xbf5c3f75,0xbf03be95,0xbf193f7f,0xbf4d3dc6,0x3f183e49,0xbf4e3f7b,0x3f5bbe46,0xbf043f7b,
0x3f3ebf7f,0x3f2c3dcc,0x3edcbf75,0x3f67be94,0xbf3dbac9,0x3f2cbf80,0xbf713ec3,0x3eadbf6d,0xbec5beac,0x3f6cbf71,0xbac9bf2c,0x3f80bf3e,
0xbf753f68,0xbe95beda,0xbf7f3f2c,0x3dc6bf3d,0x3e493f03,0xbf7b3f5c,0xbe463f4d,0xbf7b3f19,0x3f7fbf4e,0x3dcc3f18,0x3f75bf04,0xbe943f5b,
0x3f78bf6d,0x3e7d3ec2,0x3f19bb97,0xbf4d3f80,0x3d36bf21,0x3f80bf47,0x3f71bf75,0x3eaf3e92,0xbf713f0f,0x3eaabf54,0xbd5cbf0d,0x3f80bf56,
0xbf183f75,0xbf4e3e97,0xbf793f23,0x3e74bf45,0x3dd83ed7,0xbf7f3f68,0xbf763f2d,0x3e91bf3c,0x3f6dbf1a,0xbec03f4c,0xbf343f78,0xbf363e80,
0x3f45bf7d,0x3f24be1e,0x3e983e71,0xbf743f79,0xbe4fbea9,0x3f7bbf72,0x3f7bbf3f,0xbe403f2a,0xbf803f63,0x3d1dbeec,0x3f70bf7f,0x3eb23db3,
0xbf2a3f6b,0xbf403ec9,0x3ea7bf33,0x3f72bf37,0x3e213e8f,0xbf7d3f76,0xbf063ddf,0x3f5abf7e,0x3f5dbf11,0xbf013f53,0xbf7e3f56,0x3e0bbf0c,
0x3e3abf01,0x3f7cbf5d,0xbf0b3f4b,0xbf573f1b,0xbef83e24,0x3f60bf7d,0x3de53e6b,0xbf7e3f79,0xbf6e3f40,0x3ebdbf29,0x3f38bee1,0xbf333f66,
0xbf743f80,0xbe9bbd10,0x3f7fbf69,0xbdad3ed4,0x3f72bf57,0xbea43f0b,0xbd87be37,0x3f7fbf7c,0x3f7dbf7f,0x3e273da6,0xbf073e9d,0x3f59bf74,
0x3f4bbf6b,0x3f1cbecc,0xbf5e3f38,0x3f00bf32,0x3ed3bf1f,0x3f69bf49,0xbf803f76,0x3d04be8c,0xbee83f14,0xbf643f51,0x3f26bf08,0xbf433f59,
0xbe343ea3,0xbf7c3f73,0x3f58bf41,0xbf0a3f28,0x3df13cef,0xbf7e3f80,0x3f76bf6a,0xbe8b3ed2,0x3ecdbe86,0xbf6b3f77,0x3f80bf7e,0x3ca33e02,
0xbf513f4a,0x3f14bf1e,0xbf7a3f77,0x3e62be89,0xbf5f3f58,0x3efdbf09,0xbf7e3f7c,0x3dfebe31,0xbf6a3f64,0x3ed0bee7,0xbf803f7f,0x3cd6bd9a,
0xbf733f6f,0x3ea1beb9,0xbf7f3f80,0xbd943cbc,0x3bfb3bff,0x2c6aa5e4,0x2c6a25e4,0xbbfb3bff,0x3be53bf2,0x3122af59,0x31222f59,0xbbe53bf2,
0x3bbf3bd4,0x3402b294,0x34023294,0xbbbf3bd4,0x3b873ba5,0x356ab4b7,0x356a34b7,0xbb873ba5,0x3bd03bfb,0x32deac9c,0x32de2c9c,0xbbd03bfb,
0x3b013b7c,0x37bdb5a5,0x37bd35a5,0xbb013b7c,0x399d3a60,0x39b3b8d6,0x39b338d6,0xb99d3a60,0x378538bc,0x3b10ba73,0x3b103a73,0xb78538bc,
0x3b7a3bf1,0x35b1afbd,0x35b12fbd,0xbb7a3bf1,0x394a3a93,0x3a00b88e,0x3a00388e,0xb94a3a93,0x33893764,0x3bc6bb18,0x3bc63b18,0xb3893764,
0xb3d39cb6,0x3bc2bc00,0x3bc23c00,0x33d39cb6,0x3afb3be2,0x37d2b16c,0x37d2316c,0xbafb3be2,0x35eb3946,0x3b6fba04,0x3b6f3a04,0xb5eb3946,
0xb4c328e8,0x3ba3bbfe,0x3ba33bfe,0x34c328e8,0xbaa9b8cc,0x386fba67,0x386f3a67,0x3aa9b8cc,0x3a543bcf,0x38e5b2f7,0x38e532f7,0xba543bcf,
0x2884374e,0x3bffbb1e,0x3bff3b1e,0xa884374e,0xb9f8b648,0x3954bb5c,0x39543b5c,0x39f8b648,0xbbe9bbab,0xb0beb493,0xb0be3493,0x3be9bbab,
0x398b3bb7,0x39c5b43e,0x39c5343e,0xb98b3bb7,0xb4db3340,0x3b9fbbcb,0x3b9f3bcb,0x34db3340,0xbbdcb9fc,0x3201b94f,0x3201394f,0x3bdcb9fc,
0xb911bb85,0xba313576,0xba31b576,0x3911bb85,0x38a33b9a,0x3a85b4ff,0x3a8534ff,0xb8a33b9a,0xb8dba452,0x3a5cbc00,0x3a5c3c00,0x38dba452,
0xbb83bbae,0xb581b47b,0xb581347b,0x3b83bbae,0x2a7ab86a,0xbbfd3aac,0xbbfdbaac,0xaa7ab86a,0x37423b78,0x3b21b5bc,0x3b2135bc,0xb7423b78,
0xbab6b426,0x385abbba,0x385a3bba,0x3ab6b426,0xb907bbe6,0xba393109,0xba39b109,0x3907bbe6,0x39aa2ade,0xb9a63bfd,0xb9a6bbfd,0xb9aa2ade,
0x35173b52,0x3b96b676,0x3b963676,0xb5173b52,0xbbc9b7c8,0x3359bafe,0x33593afe,0x3bc9b7c8,0xb074ba9b,0xbbec3884,0xbbecb884,0x3074ba9b,
0x3bfe391b,0xaa163a29,0xaa16ba29,0xbbfe391b,0x319e3b27,0x3be0b72c,0x3be0372c,0xb19e3b27,0xbbf3b979,0xaf27b9d6,0xaf2739d6,0x3bf3b979,
0x363cb80a,0xbb5e3ae8,0xbb5ebae8,0xb63cb80a,0x3a2d3bc5,0x391633a2,0x3916b3a2,0xba2d3bc5,0x27763af7,0x3bffb7dd,0x3bff37dd,0xa7763af7,
0xbb2fbaba,0xb70ab855,0xb70a3855,0x3b2fbaba,0x3a76ad97,0xb8b73bf8,0xb8b7bbf8,0xba76ad97,0x30a63b60,0x3beab631,0x3bea3631,0xb0a63b60,
0xaf8b3ac4,0x3bf2b845,0x3bf23845,0x2f8b3ac4,0xb994bb94,0xb9bcb523,0xb9bc3523,0x3994bb94,0x3bf8358d,0xadc93b81,0xadc9bb81,0xbbf8358d,
0xb8743815,0x3aa5bae1,0x3aa53ae1,0x38743815,0xb4323a8c,0x3bb8b899,0x3bb83899,0x34323a8c,0xb6a4bbf9,0xbb47ad33,0xbb472d33,0x36a4bbf9,
0x3b3539b8,0x36f43999,0x36f4b999,0xbb3539b8,0xbbc3ae91,0x33babbf5,0x33ba3bf5,0x3bc3ae91,0xb66b3a50,0x3b54b8ea,0x3b5438ea,0x366b3a50,
0xad65bbe4,0xbbf9313b,0xbbf9b13b,0x2d65bbe4,0x38653b90,0x3ab0353a,0x3ab0b53a,0xb8653b90,0xbb0db966,0xb790b9e7,0xb79039e7,0x3b0db966,
0xb8403a11,0x3ac7b937,0x3ac73937,0x38403a11,0x341abb57,0xbbbc365f,0xbbbcb65f,0xb41abb57,0x294d3bf4,0x3bfeaef5,0x3bfe2ef5,0xa94d3bf4,
0xb55ebbda,0xbb89b219,0xbb893219,0x355ebbda,0xb93339cd,0x3a15b982,0x3a153982,0x393339cd,0x3889ba58,0xba9738e0,0xba97b8e0,0xb889ba58,
0xb7a63ad1,0x3b07b830,0x3b073830,0x37a63ad1,0x3625bb37,0xbb6336e8,0xbb63b6e8,0xb625bb37,0xba093986,0x3941b9c9,0x394139c9,0x3a093986,
0x3a7eb8f8,0xb8ad3a45,0xb8adba45,0xba7eb8f8,0xbae5385f,0x380fbab3,0x380f3ab3,0x3ae5385f,0x3b3db77a,0xb6d23b13,0xb6d2bb13,0xbb3db77a,
0xbabd393c,0x3850ba0d,0x38503a0d,0x3abd393c,0x3bb0b699,0xb46f3b4a,0xb46fbb4a,0xbbb0b699,0xbc00305b,0x9fdbbbed,0x9fdb3bed,0x3c00305b,
0x3ba730d7,0x34ab3be8,0x34abbbe8,0xbba730d7,0xbb4c38ee,0x368dba4d,0x368d3a4d,0x3b4c38ee,0x3bfcb1b6,0x2c063bdf,0x2c06bbdf,0xbbfcb1b6,
0xbad5b4cf,0xb82abba1,0xb82a3ba1,0x3ad5b4cf,0x381a39af,0x3ade39a1,0x3adeb9a1,0xb81a39af,0xbbb3389e,0x3457ba89,0x34573a89,0x3bb3389e,
0x3b592c38,0x36543bfc,0x3654bbfc,0xbb592c38,0xb76fb970,0xbb16b9df,0xbb1639df,0x376fb970,0xb24b3beb,0x3bd8308d,0x3bd8b08d,0x324b3beb,
0xbbef384a,0x3010bac1,0x30103ac1,0x3bef384a,0x39da34e7,0x39743b9e,0x3974bb9e,0xb9da34e7,0x2b43bb6c,0xbbfdb5f7,0xbbfd35f7,0xab43bb6c,
0xba6f3b0a,0x38c1b79b,0x38c1379b,0x3a6f3b0a,0xbc0037e8,0xa51bbaf4,0xa51b3af4,0x3c0037e8,0x3759383a,0x3b1b3acb,0x3b1bbacb,0xb759383a,
0x387fbbfc,0xba9e2ba7,0xba9eaba7,0xb87fbbfc,0xbbf636c6,0xae5fbb3f,0xae5f3b3f,0x3bf636c6,0xbbe33737,0xb153bb24,0xb1533b24,0x3be33737,
0x304239c0,0x3bee3990,0x3beeb990,0xb04239c0,0x3b42bb04,0xb6bb37b2,0xb6bbb7b2,0xbb42bb04,0xb95db263,0xb9f0bbd7,0xb9f03bd7,0x395db263,
0xbb9c3682,0xb4f3bb4f,0xb4f33b4f,0x3b9c3682,0xb2ad3aee,0x3bd337fe,0x3bd3b7fe,0x32ad3aee,0x3bf5b8b2,0x2ec33a7a,0x2ec3ba7a,0xbbf5b8b2,
0x1648b9f4,0xbc00b958,0xbc003958,0x9648b9f4,0xbb2a35c8,0xb721bb76,0xb7213b76,0x3b2a35c8,0xb8353bb2,0x3ace3463,0x3aceb463,0x38353bb2,
0x3a64b1e8,0x38d13bdd,0x38d1bbdd,0xba64b1e8,0x3962bbf7,0xb9ebadfb,0xb9eb2dfb,0xb962bbf7,0xba90350b,0xb894bb98,0xb8943b98,0x3a90350b,
0xba413bff,0x38fd281f,0x38fda81f,0x3a413bff,0x3602340e,0x3b6a3bbd,0x3b6abbbd,0xb602340e,0x3bf6bad8,0xae2d3825,0xae2db825,0xbbf6bad8,
0xb9d2344b,0xb97dbbb5,0xb97d3bb5,0x39d2344b,0xbb923bd2,0x352fb2c6,0x352f32c6,0x3b923bd2,0xb0f03924,0x3be73a21,0x3be7ba21,0x30f03924,
0x3a6bb60e,0x38c73b68,0x38c7bb68,0xba6bb60e,0xb8f3330f,0xba49bbce,0xba493bce,0x38f3330f,0xbc003b2c,0xa311b715,0xa3113715,0x3c003b2c,
0xb91f3b45,0x3a2536af,0x3a25b6af,0x391f3b45,0x323233eb,0x3bd93bc0,0x3bd9bbc0,0xb23233eb,0xb7f33185,0xbaf1bbe1,0xbaf13be1,0x37f33185,
0xbb7f3a19,0xb599b92e,0xb599392e,0x3b7f3a19,0xbb8e3c00,0x3546a17f,0x3546217f,0x3b8e3c00,0xb8203a35,0x3adb390c,0x3adbb90c,0x38203a35,
0xb5d42fef,0xbb73bbf0,0xbb733bf0,0x35d42fef,0xba1d38a8,0xb929ba81,0xb9293a81,0x3a1d38a8,0xbbd63b32,0xb27cb6ff,0xb27c36ff,0x3bd63b32,
0xbba93bfe,0x349f29b1,0x349fa9b1,0x3ba93bfe,0xb3282cce,0xbbccbbfa,0xbbcc3bfa,0x33282cce,0xb80535df,0xbaebbb71,0xbaeb3b71,0x380535df,
0xb9e33902,0xb96bba3d,0xb96b3a3d,0x39e33902,0xbb3a3aa2,0xb6ddb87a,0xb6dd387a,0x3b3a3aa2,0xad0026ad,0xbbfabbff,0xbbfa3bff,0x2d0026ad,
0xb1cf3029,0xbbdebbef,0xbbde3bef,0x31cf3029,0xb4873371,0xbbacbbc8,0xbbac3bc8,0x34873371,0xb61a3552,0xbb65bb8b,0xbb653b8b,0x361a3552,
0x3b3f3b65,0x36c6b61a,0x36c6361a,0xbb3f3b65,0x3ae83b16,0x380ab76f,0x380a376f,0xbae83b16,0x3a813ab6,0x38a8b85a,0x38a8385a,0xba813ab6,
0x3a0d3a49,0x393cb8f3,0x393c38f3,0xba0d3a49,0x3263356a,0x3bd7bb87,0x3bd73b87,0xb263356a,0xad972b43,0x3bf8bbfd,0x3bf83bfd,0x2d972b43,
0xb5dfb359,0x3b71bbc9,0x3b713bc9,0x35dfb359,0xb8eeb7f3,0x3a4dbaf1,0x3a4d3af1,0x38eeb7f3,0xb958b785,0x39f4bb10,0x39f43b10,0x3958b785,
0xbb81ba9e,0x358db87f,0x358d387f,0x3b81ba9e,0xbbefbbf3,0xb029af27,0xb0292f27,0x3befbbf3,0xba89bb73,0xb89e35d4,0xb89eb5d4,0x3a89bb73,
0xbbf7bbc2,0xadfbb3d3,0xadfb33d3,0x3bf7bbc2,0xb9b8bb42,0xb99936bb,0xb999b6bb,0x39b8bb42,0xaf59b70a,0xbbf23b2f,0xbbf2bb2f,0x2f59b70a,
0x384a3328,0xbac13bcc,0xbac1bbcc,0xb84a3328,0xb825baa9,0xbad8386f,0xbad8b86f,0x3825baa9,0x353aaec3,0xbb903bf5,0xbb90bbf5,0xb53aaec3,
0x3b7c3994,0xb5a539bc,0xb5a5b9bc,0xbb7c3994,0x3af43bfa,0x37e8ad00,0x37e82d00,0xbaf43bfa,0x360eb0be,0xbb683be9,0xbb68bbe9,0xb60eb0be,
0x3bf43a64,0xaef538d1,0xaef5b8d1,0xbbf43a64,0x388e3b47,0x3a93b6a4,0x3a9336a4,0xb88e3b47,0xb7372c6a,0x3b24bbfb,0x3b243bfb,0x37372c6a,
0x3bc03911,0xb3eb3a31,0xb3ebba31,0xbbc03911,0x38303b6a,0x3ad1b602,0x3ad13602,0xb8303b6a,0xb946ad65,0x3a04bbf9,0x3a043bf9,0x3946ad65,
0xbb4fbbd0,0xb682b2de,0xb68232de,0x3b4fbbd0,0x3a353bfd,0x390c2a7a,0x390caa7a,0xba353bfd,0xb85f30f0,0x3ab3bbe7,0x3ab33be7,0x385f30f0,
0xbb1ebbbc,0xb74eb41a,0xb74e341a,0x3b1ebbbc,0x35c8b5b1,0xbb763b7a,0xbb76bb7a,0xb5c8b5b1,0xa9b139aa,0x3bfeb9a6,0x3bfe39a6,0x29b139aa,
0xbbedba25,0xb05bb91f,0xb05b391f,0x3bedba25,0x3340b889,0xbbcb3a97,0xbbcbba97,0xb340b889,0x3b983afb,0x350b37d2,0x350bb7d2,0xbb983afb,
0xbaa2aa16,0x387abbfe,0x387a3bfe,0x3aa2aa16,0xb4cfbb8e,0xbba13546,0xbba1b546,0x34cfbb8e,0x3c0038ad,0xa4523a7e,0xa452ba7e,0xbc0038ad,
0xb44b38e5,0x3bb5ba54,0x3bb53a54,0x344b38e5,0xbb8bba2d,0xb552b916,0xb5523916,0x3b8bba2d,0x39dfb27c,0xb9703bd6,0xb970bbd6,0xb9dfb27c,
0x34263bb0,0x3bbab46f,0x3bba346f,0xb4263bb0,0xbbceb98b,0xb30fb9c5,0xb30f39c5,0x3bceb98b,0xb4b7bbea,0xbba530a6,0xbba5b0a6,0x34b7bbea,
0x3b6c39e3,0x35f7396b,0x35f7b96b,0xbb6c39e3,0xbafe2c06,0x37c8bbfc,0x37c83bfc,0x3afe2c06,0x3185ba85,0xbbe138a3,0xbbe1b8a3,0xb185ba85,
0x38bcb874,0xba733aa5,0xba73baa5,0xb8bcb874,0x2ba73bac,0x3bfcb487,0x3bfc3487,0xaba73bac,0xb979bb59,0xb9d6b654,0xb9d63654,0x3979bb59,
0x3bf03742,0x2fef3b21,0x2fefbb21,0xbbf03742,0x3c0033ba,0x9cb63bc3,0x9cb6bbc3,0xbc0033ba,0xbb043402,0x37b2bbbf,0x37b23bbf,0x3b043402,
0x3855b974,0xbaba39da,0xbabab9da,0xb855b974,0xacce3b96,0x3bfab517,0x3bfa3517,0x2cce3b96,0x38cc3b0d,0x3a673790,0x3a67b790,0xb8cc3b0d,
0xba7ab99d,0xb8b2b9b3,0xb8b239b3,0x3a7ab99d,0x3b943759,0x35233b1b,0x3523bb1b,0xbb943759,0xbbffb19e,0xa6adbbe0,0xa6ad3be0,0x3bffb19e,
0xb4933b89,0x3babb55e,0x3bab355e,0x34933b89,0x31e8bbc6,0xbbdd3389,0xbbddb389,0xb1e8bbc6,0xad333bee,0x3bf9b042,0x3bf93042,0x2d333bee,
0xa5e4bbff,0xbbff2776,0xbbffa776,0x25e4bbff,0xbb853625,0x3576bb63,0x35763b63,0x3b853625,0x3bbdb4c3,0xb40e3ba3,0xb40ebba3,0xbbbdb4c3,
0xbbe432ad,0x313bbbd3,0x313b3bd3,0x3be432ad,0x3bfbaf8b,0xac9c3bf2,0xac9cbbf2,0xbbfbaf8b,0xbaacb6d2,0xb86abb3d,0xb86a3b3d,0x3aacb6d2,
0x39243954,0x3a2139f8,0x3a21b9f8,0xb9243954,0xb65fbace,0xbb57b835,0xbb573835,0x365fbace,0x2fbd3bb8,0x3bf13432,0x3bf1b432,0xafbd3bb8,
0xaadebba7,0xbbfdb4ab,0xbbfd34ab,0x2adebba7,0xb6af3bdc,0x3b45b201,0x3b453201,0x36af3bdc,0x3a58ba41,0xb8e038fd,0xb8e0b8fd,0xba58ba41,
0xbbe2366b,0x316cbb54,0x316c3b54,0x3be2366b,0x3a29bade,0xb91b381a,0xb91bb81a,0xba29bade,0xbc003581,0x217fbb83,0x217f3b83,0x3c003581,
0x3a45352f,0x38f83b92,0x38f8bb92,0xba45352f,0xb2f7bac7,0xbbcfb840,0xbbcf3840,0x32f7bac7,0x3bc5b24b,0x33a23bd8,0x33a2bbd8,0xbbc5b24b,
0xb6ffb907,0xbb32ba39,0xbb323a39,0x36ffb907,0xb6993c00,0x3b4a2311,0x3b4aa311,0x36993c00,0x3bb7b933,0xb43e3a15,0xb43eba15,0xbbb7b933,
0x363138c1,0x3b603a6f,0x3b60ba6f,0xb63138c1,0x3902bbec,0xba3d3074,0xba3db074,0xb902bbec,0xbbdf3599,0xb1b6bb7f,0xb1b63b7f,0x3bdf3599,
0x34ff3941,0x3b9a3a09,0x3b9aba09,0xb4ff3941,0xb8153bf6,0x3ae12e5f,0x3ae1ae5f,0x38153bf6,0x3bc8b63c,0x33713b5e,0x3371bb5e,0xbbc8b63c,
0xac38ba1d,0xbbfcb929,0xbbfc3929,0x2c38ba1d,0xbb783abd,0x35bcb850,0x35bc3850,0x3b783abd,0xbbf539f0,0x2e91b95d,0x2e91395d,0x3bf539f0,
0x329438b7,0x3bd43a76,0x3bd4ba76,0xb29438b7,0x3b9ebaeb,0xb4e73805,0xb4e7b805,0xbb9ebaeb,0xb676b68d,0xbb52bb4c,0xbb523b4c,0x3676b68d,
0xb9661648,0xb9e7bc00,0xb9e73c00,0x39661648,0xba603bf8,0x38d6adc9,0x38d62dc9,0x3a603bf8,0x383a31cf,0x3acb3bde,0x3acbbbde,0xb83a31cf,
0x3b27bbb3,0xb72c3457,0xb72cb457,0xbb27bbb3,0x3219b9eb,0xbbdab962,0xbbda3962,0xb219b9eb,0xbb1836f4,0xb764bb35,0xb7643b35,0x3b1836f4,
0xb9903be5,0x39c03122,0x39c0b122,0x39903be5,0x37dd3010,0x3af73bef,0x3af7bbef,0xb7dd3010,0x3b37bbf6,0xb6e82e2d,0xb6e8ae2d,0xbb37bbf6,
0x28e8b865,0xbbfebab0,0xbbfe3ab0,0xa8e8b865,0xbaee37bd,0xb7febb01,0xb7fe3b01,0x3aee37bd,0xbac43c00,0x3845251b,0x3845a51b,0x3ac43c00,
0x3b13b8c7,0x377a3a6b,0x377aba6b,0xbb13b8c7,0x3b5cbbfe,0xb648294d,0xb648a94d,0xbb5cbbfe,0x3463b94a,0xbbb2ba00,0xbbb23a00,0xb463b94a,
0xb8993153,0xba8cbbe3,0xba8c3be3,0x38993153,0x30d73232,0x3be83bd9,0x3be8bbd9,0xb0d73232,0x39fcb7a6,0x394f3b07,0x394fbb07,0xb9fcb7a6,
0x3bffbb6f,0x281f35eb,0x281fb5eb,0xbbffbb6f,0x3a50bb9c,0xb8eab4f3,0xb8ea34f3,0xba50bb9c,0xb9a13adb,0x39af3820,0x39afb820,0x39a13adb,
0xb47b380f,0x3bae3ae5,0x3baebae5,0x347b380f,0x32c62884,0x3bd23bff,0x3bd2bbff,0xb2c62884,0x3937b721,0x3a113b2a,0x3a11bb2a,0xb937b721,
0xbbeb3ba9,0xb08db49f,0xb08d349f,0x3beb3ba9,0xbbe63c00,0x31091fdb,0x31099fdb,0x3be63c00,0xbb2c3b9f,0x371534db,0x3715b4db,0x3b2c3b9f,
0xb9cd3a90,0x39823894,0x3982b894,0x39cd3a90,0xb79b36dd,0xbb0abb3a,0xbb0a3b3a,0x379b36dd,0xb884382a,0xba9bbad5,0xba9b3ad5,0x3884382a,
0xb92e38db,0xba19ba5c,0xba193a5c,0x392e38db,0xb9c9397d,0xb986b9d2,0xb98639d2,0x39c9397d,0x398b39cd,0x39c5b982,0x39c53982,0xb98b39cd,
0x38fd3946,0x3a41ba04,0x3a413a04,0xb8fd3946,0x386538b2,0x3ab0ba7a,0x3ab03a7a,0xb86538b2,0x37853815,0x3b10bae1,0x3b103ae1,0xb7853815,
0xba85b9c9,0x38a3b986,0x38a33986,0x3a85b9c9,0xbb92bb1e,0x352fb74e,0x352f374e,0x3b92bb1e,0xbbfebbdd,0x294db1e8,0x294d31e8,0x3bfebbdd,
0xbbc2bbf5,0xb3d32e91,0xb3d3ae91,0x3bc2bbf5,0xb742b93c,0xbb213a0d,0xbb21ba0d,0x3742b93c,0x2311b340,0xbc003bcb,0xbc00bbcb,0xa311b340,
0x37a6340e,0xbb073bbd,0xbb07bbbd,0xb7a6340e,0x3aa93966,0xb86f39e7,0xb86fb9e7,0xbaa93966,0x3b963a4d,0xb51738ee,0xb517b8ee,0xbb963a4d,
0x3b7f3c00,0x3599a452,0x35992452,0xbb7f3c00,0x380f3a21,0x3ae5b924,0x3ae53924,0xb80f3a21,0xb0be3219,0x3be9bbda,0x3be93bda,0x30be3219,
0x319e389e,0x3be0ba89,0x3be03a89,0xb19e389e,0xb929b426,0x3a1dbbba,0x3a1d3bba,0x3929b426,0xbc00bb45,0x9fdbb6af,0x9fdb36af,0x3c00bb45,
0xb911bb37,0xba3136e8,0xba31b6e8,0x3911bb37,0xbbffbac1,0x2776b84a,0x2776384a,0x3bffbac1,0xb805bafe,0xbaeb37c8,0xbaebb7c8,0x3805bafe,
0x382a217f,0xbad53c00,0xbad5bc00,0xb82a217f,0x3bfd3b13,0x2a7a377a,0x2a7ab77a,0xbbfd3b13,0x2f8bb7e8,0xbbf23af4,0xbbf2baf4,0xaf8bb7e8,
0x3bde3979,0xb1cf39d6,0xb1cfb9d6,0xbbde3979,0x376f3b32,0x3b16b6ff,0x3b1636ff,0xb76f3b32,0xb9aab0d7,0x39a6bbe8,0x39a63be8,0x39aab0d7,
0x3bb83b24,0x34323737,0x3432b737,0xbbb83b24,0xb1223855,0x3be5baba,0x3be53aba,0x31223855,0xbbfdba3d,0xab43b902,0xab433902,0x3bfdba3d,
0xaa16b9a1,0xbbfe39af,0xbbfeb9af,0x2a16b9a1,0xb66b3682,0x3b54bb4f,0x3b543b4f,0x366b3682,0xbb01bb94,0xb7bdb523,0xb7bd3523,0x3b01bb94,
0x387fb371,0xba9e3bc8,0xba9ebbc8,0xb87fb371,0x3a2d3beb,0x3916308d,0x3916b08d,0xba2d3beb,0xbac7bb76,0xb840b5c8,0xb84035c8,0x3ac7bb76,
0x3a00ad33,0xb94a3bf9,0xb94abbf9,0xba00ad33,0x36bb3bd4,0x3b42b294,0x3b423294,0xb6bb3bd4,0xbbeab79b,0x30a6bb0a,0x30a63b0a,0x3beab79b,
0x3933b50b,0xba153b98,0xba15bb98,0xb933b50b,0x35eb3be4,0x3b6fb13b,0x3b6f313b,0xb5eb3be4,0xbbf5b8d6,0xaec3ba60,0xaec33a60,0x3bf5b8d6,
0x3874b6c6,0xbaa53b3f,0xbaa5bb3f,0xb874b6c6,0x39413bb5,0x3a09344b,0x3a09b44b,0xb9413bb5,0xbbffb65f,0x2884bb57,0x28843b57,0x3bffb65f,
0x38d1b764,0xba643b18,0xba64bb18,0xb8d1b764,0x33ba3bd7,0x3bc3b263,0x3bc33263,0xb3ba3bd7,0xbabd330f,0x3850bbce,0x38503bce,0x3abd330f,
0x34dbba58,0xbb9f38e0,0xbb9fb8e0,0xb4dbba58,0x36023bfe,0x3b6a28e8,0x3b6aa8e8,0xb6023bfe,0xbb0db9f4,0xb790b958,0xb7903958,0x3b0db9f4,
0xb68dbbe1,0xbb4cb185,0xbb4c3185,0x368dbbe1,0x3a5c3a45,0x38db38f8,0x38dbb8f8,0xba5c3a45,0xbbe7b648,0xb0f0bb5c,0xb0f03b5c,0x3be7b648,
0x3b89adfb,0xb55e3bf7,0xb55ebbf7,0xbb89adfb,0x3bb3afef,0xb4573bf0,0xb457bbf0,0xbbb3afef,0xbab63699,0x385abb4a,0x385a3b4a,0x3ab63699,
0x391fb94f,0xba2539fc,0xba25b9fc,0xb91fb94f,0xb6253ad8,0x3b63b825,0x3b633825,0x36253ad8,0x30103bfa,0x3bef2cce,0x3befacce,0xb0103bfa,
0xb359bbdf,0xbbc9b1b6,0xbbc931b6,0x3359bbdf,0x35463bae,0x3b8e347b,0x3b8eb47b,0xb5463bae,0xb6d2bb68,0xbb3db60e,0xbb3d360e,0x36d2bb68,
0xbc0026ad,0xa51bbbff,0xa51b3bff,0x3c0026ad,0x3bf32c38,0x2f273bfc,0x2f27bbfc,0xbbf32c38,0xbbd6b109,0xb27cbbe6,0xb27c3be6,0x3bd6b109,
0x3ba733eb,0x34ab3bc0,0x34abbbc0,0xbba733eb,0x3153bbff,0xbbe325e4,0xbbe3a5e4,0xb153bbff,0xb70a3b9e,0x3b2fb4e7,0x3b2f34e7,0x370a3b9e,
0x396bba9b,0xb9e33884,0xb9e3b884,0xb96bba9b,0xbade390c,0x381aba35,0x381a3a35,0x3ade390c,0x3b9c2c9c,0x34f33bfb,0x34f3bbfb,0xbb9c2c9c,
0xb994b83a,0xb9bcbacb,0xb9bc3acb,0x3994b83a,0x34873ae8,0x3bac380a,0x3bacb80a,0xb4873ae8,0x324bbbfe,0xbbd8a9b1,0xbbd829b1,0xb24bbbfe,
0xb7213bf1,0x3b2aafbd,0x3b2a2fbd,0x37213bf1,0x3b47b990,0xb6a439c0,0xb6a4b9c0,0xbb47b990,0xbbbf2d97,0xb402bbf8,0xb4023bf8,0x3bbf2d97,
0x38c1387a,0x3a6f3aa2,0x3a6fbaa2,0xb8c1387a,0xba90b16c,0xb894bbe2,0xb8943be2,0x3a90b16c,0x2d653aee,0x3bf937fe,0x3bf9b7fe,0xad653aee,
0x39b3bb81,0xb99d358d,0xb99db58d,0xb9b3bb81,0xbbf63552,0xae5fbb8b,0xae5f3b8b,0x3bf63552,0x397dbbcf,0xb9d232f7,0xb9d2b2f7,0xb97dbbcf,
0xbbbc3463,0xb41abbb2,0xb41a3bb2,0x3bbc3463,0x338939b8,0x3bc63999,0x3bc6b999,0xb38939b8,0x39f0bba5,0xb95d34b7,0xb95db4b7,0xb9f0bba5,
0x38f3343e,0x3a493bb7,0x3a49bbb7,0xb8f3343e,0x3889bbff,0xba97a81f,0xba97281f,0xb889bbff,0xbba3353a,0xb4c3bb90,0xb4c33b90,0x3ba3353a,
0x96483a73,0x3c0038bc,0x3c00b8bc,0x16483a73,0xbaf13b9a,0x37f3b4ff,0x37f334ff,0x3af13b9a,0x38ad32c6,0x3a7e3bd2,0x3a7ebbd2,0xb8ad32c6,
0x39f8bbf4,0xb9542ef5,0xb954aef5,0xb9f8bbf4,0xb9eb9cb6,0xb962bc00,0xb9623c00,0x39eb9cb6,0xb5d4b5bc,0xbb73bb78,0xbb733b78,0x35d4b5bc,
0xbbb03b2c,0x346fb715,0x346f3715,0x3bb03b2c,0x32013830,0x3bdc3ad1,0x3bdcbad1,0xb2013830,0x3bf6ba67,0xae2d38cc,0xae2db8cc,0xbbf6ba67,
0x3bccbb52,0xb3283676,0xb328b676,0xbbccbb52,0x2c06b92e,0xbbfcba19,0xbbfc3a19,0xac06b92e,0xbb83385f,0xb581bab3,0xb5813ab3,0x3b83385f,
0xb8c73bab,0x3a6b3493,0x3a6bb493,0x38c73bab,0x2d00372c,0x3bfa3b27,0x3bfabb27,0xad00372c,0x3b59b8a8,0x36543a81,0x3654ba81,0xbb59b8a8,
0x3a39bbed,0xb907b05b,0xb907305b,0xba39bbed,0xb232b576,0xbbd9bb85,0xbbd93b85,0x3232b576,0xbbfb3af7,0xac6ab7dd,0xac6a37dd,0x3bfb3af7,
0xb9743b71,0x39da35df,0x39dab5df,0x39743b71,0x307434cf,0x3bec3ba1,0x3becbba1,0xb07434cf,0x3adbb86a,0x38203aac,0x3820baac,0xbadbb86a,
0x32deb845,0xbbd0bac4,0xbbd03ac4,0xb2deb845,0xb7593029,0xbb1bbbef,0xbb1b3bef,0x37593029,0xbb5e39df,0xb63cb970,0xb63c3970,0x3b5e39df,
0xbba93bfd,0x349faade,0x349f2ade,0x3ba93bfd,0x3b7aba8c,0x35b13899,0x35b1b899,0xbb7aba8c,0x3beebbf2,0xb0422f59,0xb042af59,0xbbeebbf2,
0x3a76bb6c,0xb8b7b5f7,0xb8b735f7,0xba76bb6c,0x36ddb91b,0xbb3aba29,0xbb3a3a29,0xb6ddb91b,0xb7d238ea,0x3afb3a50,0x3afbba50,0x37d238ea,
0xb2ad35a5,0x3bd33b7c,0x3bd3bb7c,0x32ad35a5,0x2dc92ba7,0x3bf83bfc,0x3bf8bbfc,0xadc92ba7,0x361ab3a2,0x3b653bc5,0x3b65bbc5,0xb61ab3a2,
0xba543a11,0xb8e5b937,0xb8e53937,0x3a543a11,0xbace3a93,0xb835b88e,0xb835388e,0x3ace3a93,0xbb353b04,0xb6f4b7b2,0xb6f437b2,0x3b353b04,
0xbb873b60,0xb56ab631,0xb56a3631,0x3b873b60,0x363136dd,0x3b60bb3a,0x3b603b3a,0xb63136dd,0x34cf3581,0x3ba1bb83,0x3ba13b83,0xb4cf3581,
0x32c6341a,0x3bd2bbbc,0x3bd23bbc,0xb2c6341a,0x2fbd3153,0x3bf1bbe3,0x3bf13be3,0xafbd3153,0xbae1bb65,0xb815361a,0xb815b61a,0x3ae1bb65,
0xb970ba39,0xb9df3907,0xb9dfb907,0x3970ba39,0xb715b889,0xbb2c3a97,0xbb2cba97,0x3715b889,0xb16cb4f3,0xbbe23b9c,0xbbe2bb9c,0x316cb4f3,
0x3bf53b87,0xae91356a,0xae91b56a,0xbbf53b87,0x3b6c3bec,0x35f7b074,0x35f73074,0xbb6c3bec,0x392e3a7e,0x3a19b8ad,0x3a1938ad,0xb92e3a7e,
0x32f73721,0x3bcfbb2a,0x3bcf3b2a,0xb2f73721,0xb9e7b785,0x3966bb10,0x39663b10,0x39e7b785,0xbbfcbb5e,0x2ba7b63c,0x2ba7363c,0x3bfcbb5e,
0xba81bbb0,0xb8a8346f,0xb8a8b46f,0x3a81bbb0,0xb43eb894,0xbbb73a90,0xbbb7ba90,0x343eb894,0x3219b3d3,0xbbda3bc2,0xbbdabbc2,0xb219b3d3,
0x3b0438b7,0xb7b23a76,0xb7b2ba76,0xbb0438b7,0x3b713bfc,0x35df2c06,0x35dfac06,0xbb713bfc,0x34ff397d,0x3b9ab9d2,0x3b9a39d2,0xb4ff397d,
0x36e83aa9,0x3b37b86f,0x3b37386f,0xb6e83aa9,0xb8b2adc9,0x3a7abbf8,0x3a7a3bf8,0x38b2adc9,0xbbefbb59,0xb029b654,0xb0293654,0x3befbb59,
0xb5bcba49,0xbb7838f3,0xbb78b8f3,0x35bcba49,0xbb13bbe9,0xb77ab0be,0xb77a30be,0x3b13bbe9,0x31e8b6f4,0xbbdd3b35,0xbbddbb35,0xb1e8b6f4,
0x3bf239da,0xaf593974,0xaf59b974,0xbbf239da,0x36763af1,0x3b52b7f3,0x3b5237f3,0xb6763af1,0x3be83911,0xb0d73a31,0xb0d7ba31,0xbbe83911,
0x340e3ab0,0x3bbdb865,0x3bbd3865,0xb40e3ab0,0xbb7cb759,0x35a5bb1b,0x35a53b1b,0x3b7cb759,0xb72cbb73,0xbb2735d4,0xbb27b5d4,0x372cbb73,
0xb9a12a7a,0x39afbbfd,0x39af3bfd,0x39a12a7a,0xb924bbfe,0xba21294d,0xba21a94d,0x3924bbfe,0x3a933042,0xb88e3bee,0xb88ebbee,0xba933042,
0x37dd3bcc,0x3af7b328,0x3af73328,0xb7dd3bcc,0x308db9aa,0xbbeb39a6,0xbbebb9a6,0xb08db9aa,0x3b453b07,0x36af37a6,0x36afb7a6,0xbb453b07,
0xb94632ad,0x3a04bbd3,0x3a043bd3,0x394632ad,0xb845bbfa,0xbac42d00,0xbac4ad00,0x3845bbfa,0x379b3bfe,0x3b0aaa16,0x3b0a2a16,0xb79b3bfe,
0xbc00b80f,0x217fbae5,0x217f3ae5,0x3c00b80f,0x374eb835,0xbb1e3ace,0xbb1ebace,0xb74eb835,0x38993bfb,0x3a8c2c6a,0x3a8cac6a,0xb8993bfb,
0xbb3fba2d,0xb6c6b916,0xb6c63916,0x3b3fba2d,0x3b329fdb,0xb6ff3c00,0xb6ffbc00,0xbb329fdb,0xb3403a41,0x3bcbb8fd,0x3bcb38fd,0x33403a41,
0xb8eabbd0,0xba50b2de,0xba5032de,0x38eabbd0,0x3bd730a6,0xb2633bea,0xb263bbea,0xbbd730a6,0xb902382a,0x3a3dbad5,0x3a3d3ad5,0x3902382a,
0xa452bb92,0xbc00352f,0xbc00b52f,0x2452bb92,0x39373b7a,0x3a1135b1,0x3a11b5b1,0xb9373b7a,0xb9583874,0x39f4baa5,0x39f43aa5,0x39583874,
0x3371bb16,0xbbc8376f,0xbbc8b76f,0xb371bb16,0x34263c00,0x3bba2311,0x3bbaa311,0xb4263c00,0xb982bafb,0xb9cdb7d2,0xb9cd37d2,0x3982bafb,
0x2dfbbbc3,0xbbf733ba,0xbbf7b3ba,0xadfbbbc3,0x32943bfd,0x3bd42b43,0x3bd4ab43,0xb2943bfd,0xb7c8bb7f,0xbafeb599,0xbafe3599,0x37c8bb7f,
0x39c93a54,0x398638e5,0x3986b8e5,0xb9c93a54,0x38253b0d,0x3ad83790,0x3ad8b790,0xb8253b0d,0xb8d6ba9e,0xba60b87f,0xba60387f,0x38d6ba9e,
0x39793a1d,0x39d63929,0x39d6b929,0xb9793a1d,0xba0db98b,0xb93cb9c5,0xb93c39c5,0x3a0db98b,0xbb68b55e,0xb60ebb89,0xb60e3b89,0x3b68b55e,
0x3b1836bb,0x37643b42,0x3764bb42,0xbb1836bb,0xbabab805,0xb855baeb,0xb8553aeb,0x3abab805,0x3a4d38a3,0x38ee3a85,0x38eeba85,0xba4d38a3,
0x3bc0b625,0xb3eb3b63,0xb3ebbb63,0xbbc0b625,0xbbfe2ec3,0xa8e8bbf5,0xa8e83bf5,0x3bfe2ec3,0x3b9431cf,0x35233bde,0x3523bbde,0xbb9431cf,
0xba89b742,0xb89ebb21,0xb89e3b21,0x3a89b742,0xb90c3b3d,0x3a35b6d2,0x3a3536d2,0x390c3b3d,0x3b5cb8d1,0xb6483a64,0xb648ba64,0xbb5cb8d1,
0xbbf93122,0xad33bbe5,0xad333be5,0x3bf93122,0x3ac13517,0x384a3b96,0x384abb96,0xbac13517,0x29b1bba7,0xbbfeb4ab,0xbbfe34ab,0xa9b1bba7,
0xb94f3b6a,0x39fcb602,0x39fc3602,0x394f3b6a,0x3be4b7bd,0xb13b3b01,0xb13bbb01,0xbbe4b7bd,0xbaf4b19e,0xb7e8bbe0,0xb7e83be0,0x3af4b19e,
0x387a381a,0x3aa23ade,0x3aa2bade,0xb87a381a,0x347bbbe7,0xbbaeb0f0,0xbbae30f0,0xb47bbbe7,0xbb573a00,0x365fb94a,0x365f394a,0x3b573a00,
0x3b242776,0x37373bff,0x3737bbff,0xbb242776,0xbb8b324b,0xb552bbd8,0xb5523bd8,0x3b8b324b,0x31093a25,0x3be6391f,0x3be6b91f,0xb1093a25,
0x3a58bb6f,0xb8e035eb,0xb8e0b5eb,0xba58bb6f,0xbb4f2f8b,0xb682bbf2,0xb6823bf2,0x3b4f2f8b,0x3ba5ba6f,0xb4b738c1,0xb4b7b8c1,0xbba5ba6f,
0xb884b546,0xba9bbb8e,0xba9b3b8e,0x3884b546,0xb8f83bff,0x3a45a884,0x3a452884,0x38f83bff,0x3b76b432,0x35c83bb8,0x35c8bbb8,0xbb76b432,
0xb8bc3bf6,0x3a732e5f,0x3a73ae5f,0x38bc3bf6,0x3ae8b27c,0x380a3bd6,0x380abbd6,0xbae8b27c,0x3699bb9f,0xbb4ab4db,0xbb4a34db,0xb699bb9f,
0xbb98366b,0xb50bbb54,0xb50b3b54,0x3b98366b,0x9cb6b95d,0xbc00b9f0,0xbc0039f0,0x1cb6b95d,0xbbf8396b,0xad97b9e3,0xad9739e3,0x3bf8396b,
0xb1b63a5c,0x3bdf38db,0x3bdfb8db,0x31b63a5c,0x3bb5b840,0x344b3ac7,0x344bbac7,0xbbb5b840,0x38cc9648,0x3a673c00,0x3a67bc00,0xb8cc9648,
0x3b81bbac,0xb58d3487,0xb58db487,0xbb81bbac,0xac38b85a,0xbbfcbab6,0xbbfc3ab6,0x2c38b85a,0xbbce3933,0xb30fba15,0xb30f3a15,0x3bce3933,
0xbbab3962,0xb493b9eb,0xb49339eb,0x3bab3962,0xb9993bbf,0x39b83402,0x39b8b402,0x39993bbf,0x34e73359,0x3b9e3bc9,0x3b9ebbc9,0xb4e73359,
0x3be1ba09,0x31853941,0x3185b941,0xbbe1ba09,0x3b85bbf6,0xb5762e2d,0xb576ae2d,0xbb85bbf6,0x353ab99d,0xbb90b9b3,0xbb9039b3,0xb53ab99d,
0xb83a2f27,0xbacbbbf3,0xbacb3bf3,0x383a2f27,0xbbf03abd,0xafefb850,0xafef3850,0x3bf03abd,0xb86a3a6b,0x3aac38c7,0x3aacb8c7,0x386a3a6b,
0x2ef53389,0x3bf43bc6,0x3bf4bbc6,0xaef53389,0x39c0b70a,0x39903b2f,0x3990bb2f,0xb9c0b70a,0x3bfabb4c,0x2cce368d,0x2cceb68d,0xbbfabb4c,
0xaadeb232,0xbbfdbbd9,0xbbfd3bd9,0x2adeb232,0xb83034c3,0xbad1bba3,0xbad13ba3,0x383034c3,0xbaee39bc,0xb7feb994,0xb7fe3994,0x3aee39bc,
0xbbff3bb3,0xa6adb457,0xa6ad3457,0x3bff3bb3,0x391bb820,0x3a293adb,0x3a29badb,0xb91bb820,0x3ab3b9f8,0x385f3954,0x385fb954,0xbab3b9f8,
0x3bb2bb47,0x346336a4,0x3463b6a4,0xbbb2bb47,0x3bffbbef,0xa5e43010,0xa5e4b010,0xbbffbbef,0xbbc53ba9,0xb3a2b49f,0xb3a2349f,0x3bc53ba9,
0xbbed3bdc,0xb05bb201,0xb05b3201,0x3bed3bdc,0xbbff3bf9,0xa81fad65,0xa81f2d65,0x3bff3bf9,0xbbfb3c00,0x2c9c251b,0x2c9ca51b,0x3bfb3c00,
0xa11ba1e4,0x18b61248,0x251b25e4,0x9cb69648,0x9f12a052,0x1d7f1bdb,0x23112452,0xa17f9fdb,0x9bdb9d7f,0x20521f12,0x1fdb217f,0xa452a311,
0x924898b6,0x21e4211b,0x16481cb6,0xa5e4a51b,0xa7a9a86b,0x1f1218b6,0x2ba72c6a,0xa3119cb6,0xa54da67b,0x242021e4,0x294d2a7a,0xa81fa5e4,
0xa1e4a420,0x267b254d,0x25e4281f,0xaa7aa94d,0x98b69f12,0x286b27a9,0x1cb62311,0xac6aaba7,0xaa63ab5f,0x21e41bdb,0x2e5f2f59,0xa5e49fdb,
0xa86ba967,0x26e024e9,0x2c6a2d65,0xaadea8e8,0xa4e9a6e0,0x2967286b,0x28e82ade,0xad65ac6a,0x9bdba1e4,0x2b5f2a63,0x1fdb25e4,0xaf59ae5f,
0xac79ad2a,0x24201d7f,0x30743122,0xa81fa17f,0xaa31ab91,0x28d026e0,0x2e2d2f8b,0xacceaade,0xa6e0a8d0,0x2b912a31,0x2ade2cce,0xaf8bae2d,
0x9d7fa420,0x2d2a2c79,0x217f281f,0xb122b074,0xadc2aea7,0x254d1f12,0x31b63294,0xa94da311,0xabf6acde,0x2a31286b,0x2fef30d7,0xae2dac6a,
0xa86baa31,0x2cde2bf6,0x2c6a2e2d,0xb0d7afef,0x9f12a54d,0x2ea72dc2,0x2311294d,0xb294b1b6,0xaf0cb012,0x267b2052,0x32f73402,0xaa7aa452,
0xacdeadf5,0x2b912967,0x30d731e8,0xaf8bad65,0xa967ab91,0x2df52cde,0x2d652f8b,0xb1e8b0d7,0xa052a67b,0x30122f0c,0x24522a7a,0xb402b2f7,
0xb02cb0d2,0x27a9211b,0x341a34b7,0xaba7a51b,0xadc2af0c,0x2c792a63,0x31b632f7,0xb074ae5f,0xaa63ac79,0x2f0c2dc2,0x2e5f3074,0xb2f7b1b6,
0xa11ba7a9,0x30d2302c,0x251b2ba7,0xb4b7b41a,0xb0d2b194,0x286b21e4,0x34b7356a,0xac6aa5e4,0xaea7b012,0x2d2a2b5f,0x32943402,0xb122af59,
0xab5fad2a,0x30122ea7,0x2f593122,0xb402b294,0xa1e4a86b,0x319430d2,0x25e42c6a,0xb56ab4b7,0xb17ab257,0x290222ad,0x3552361a,0xad00a6ad,
0xaf8cb09f,0x2ddc2c2e,0x33713487,0xb1cfb029,0xac2eaddc,0x309f2f8c,0x302931cf,0xb487b371,0xa2ada902,0x3257317a,0x26ad2d00,0xb61ab552,
0xb223b31c,0x29992376,0x35eb36c6,0xad97a776,0xb039b12d,0x2e8d2cac,0x3426350b,0xb27cb0a6,0xacacae8d,0x312d3039,0x30a6327c,0xb50bb426,
0xa376a999,0x331c3223,0x27762d97,0xb6c6b5eb,0xb2cdb3e3,0x2a312420,0x3682376f,0xae2da81f,0xb0acb1bb,0x2f3f2d2a,0x3493358d,0xb328b122,
0xad2aaf3f,0x31bb30ac,0x31223328,0xb58db493,0xa420aa31,0x33e332cd,0x281f2e2d,0xb76fb682,0xb378b456,0x2ac82484,0x3715380a,0xaec3a884,
0xb120b24a,0x2ff22da9,0x34ff360e,0xb3d3b19e,0xada9aff2,0x324a3120,0x319e33d3,0xb60eb4ff,0xa484aac8,0x34563378,0x28842ec3,0xb80ab715,
0xb413b4bc,0x2b5f24e9,0x37a6385a,0xaf59a8e8,0xb194b2da,0x30522e28,0x356a368d,0xb43eb219,0xae28b052,0x32da3194,0x3219343e,0xb68db56a,
0xa4e9ab5f,0x34bc3413,0x28e82f59,0xb85ab7a6,0xb46ab523,0x2bf6254d,0x381a38a8,0xafefa94d,0xb209b36b,0x30ac2ea7,0x35d4370a,0xb493b294,
0xaea7b0ac,0x336b3209,0x32943493,0xb70ab5d4,0xa54dabf6,0x3523346a,0x294d2fef,0xb8a8b81a,0xb4c3b58c,0x2c4725b2,0x385f38f3,0xb042a9b1,
0xb27eb3fd,0x31062f26,0x363c3785,0xb4e7b30f,0xaf26b106,0x33fd327e,0x330f34e7,0xb785b63c,0xa5b2ac47,0x358c34c3,0x29b13042,0xb8f3b85f,
0xb51cb5f6,0x2c932617,0x38a3393c,0xb08daa16,0xb2f4b448,0x31602fa5,0x36a437fe,0xb53ab389,0xafa5b160,0x344832f4,0x3389353a,0xb7feb6a4,
0xa617ac93,0x35f6351c,0x2a16308d,0xb93cb8a3,0xb577b662,0x2cde267b,0x38e53982,0xb0d7aa7a,0xb36bb493,0x31bb3012,0x370a383a,0xb58db402,
0xb012b1bb,0x3493336b,0x3402358d,0xb83ab70a,0xa67bacde,0x36623577,0x2a7a30d7,0xb982b8e5,0xb5d2b6d1,0x2d2a26e0,0x392439c5,0xb122aade,
0xb3e3b4de,0x32163052,0x376f3874,0xb5dfb43e,0xb052b216,0x34de33e3,0x343e35df,0xb874b76f,0xa6e0ad2a,0x36d135d2,0x2ade3122,0xb9c5b924,
0xb630b741,0x2d762744,0x39623a04,0xb16cab43,0xb42eb52a,0x32713092,0x37d238ad,0xb631b47b,0xb092b271,0x352a342e,0x347b3631,0xb8adb7d2,
0xa744ad76,0x37413630,0x2b43316c,0xba04b962,0xb68eb7b4,0x2dc227a9,0x399d3a41,0xb1b6aba7,0xb46ab577,0x32cd30d2,0x381a38e5,0xb682b4b7,
0xb0d2b2cd,0x3577346a,0x34b73682,0xb8e5b81a,0xa7a9adc2,0x37b4368e,0x2ba731b6,0xba41b99d,0xb6eeb815,0x2e0e2807,0x39d63a7a,0xb201ac06,
0xb4a7b5c4,0x33293113,0x384a391b,0xb6d2b4f3,0xb113b329,0x35c434a7,0x34f336d2,0xb91bb84a,0xa807ae0e,0x381536ee,0x2c063201,0xba7ab9d6,
0xb750b851,0x2e5a2839,0x3a0d3ab0,0xb24bac38,0xb4e5b613,0x33863153,0x387a394f,0xb721b52f,0xb153b386,0x361334e5,0x352f3721,0xb94fb87a,
0xa839ae5a,0x38513750,0x2c38324b,0xbab0ba0d,0xb7b4b88e,0x2ea7286b,0x3a413ae1,0xb294ac6a,0xb523b662,0x33e33194,0x38a83982,0xb76fb56a,
0xb194b3e3,0x36623523,0x356a376f,0xb982b8a8,0xa86baea7,0x388e37b4,0x2c6a3294,0xbae1ba41,0xb80db8ce,0x2ef3289e,0x3a733b10,0xb2deac9c,
0xb562b6b3,0x342031d5,0x38d639b3,0xb7bdb5a5,0xb1d5b420,0x36b33562,0x35a537bd,0xb9b3b8d6,0xa89eaef3,0x38ce380d,0x2c9c32de,0xbb10ba73,
0xb841b90f,0x2f3f28d0,0x3aa23b3a,0xb328acce,0xb5a1b705,0x344f3216,0x390239e3,0xb805b5df,0xb216b44f,0x370535a1,0x35df3805,0xb9e3b902,
0xa8d0af3f,0x390f3841,0x2cce3328,0xbb3abaa2,0xb876b952,0x2f8c2902,0x3ace3b60,0xb371ad00,0xb5e1b758,0x347e3257,0x392e3a11,0xb82ab61a,
0xb257b47e,0x375835e1,0x361a382a,0xba11b92e,0xa902af8c,0x39523876,0x2d003371,0xbb60bace,0xb8acb997,0x2fd82935,0x3af73b83,0xb3baad33,
0xb621b7ac,0x34ae3298,0x39583a3d,0xb850b654,0xb298b4ae,0x37ac3621,0x36543850,0xba3db958,0xa935afd8,0x399738ac,0x2d3333ba,0xbb83baf7,
0xb8e3b9de,0x30122967,0x3b1e3ba1,0xb402ad65,0xb662b801,0x34de32da,0x39823a67,0xb874b68d,0xb2dab4de,0x38013662,0x368d3874,0xba67b982,
0xa967b012,0x39de38e3,0x2d653402,0xbba1bb1e,0xb91cba28,0x30392999,0x3b423bbc,0xb426ad97,0xb6a4b82d,0x350e331c,0x39aa3a90,0xb899b6c6,
0xb31cb50e,0x382d36a4,0x36c63899,0xba90b9aa,0xa999b039,0x3a28391c,0x2d973426,0xbbbcbb42,0xb956ba74,0x305f29cc,0x3b633bd2,0xb44badc9,
0xb6e7b859,0x353f335e,0x39d23ab6,0xb8bcb6ff,0xb35eb53f,0x385936e7,0x36ff38bc,0xbab6b9d2,0xa9ccb05f,0x3a743956,0x2dc9344b,0xbbd2bb63,
0xb992bac3,0x308529fe,0x3b813be3,0xb46fadfb,0xb72ab886,0x357033a0,0x39f83adb,0xb8e0b737,0xb3a0b570,0x3886372a,0x373738e0,0xbadbb9f8,
0xa9feb085,0x3ac33992,0x2dfb346f,0xbbe3bb81,0xb9cfbb16,0x30ac2a31,0x3b9c3bf1,0xb493ae2d,0xb76fb8b4,0x35a133e3,0x3a1d3afe,0xb902b76f,
0xb3e3b5a1,0x38b4376f,0x376f3902,0xbafeba1d,0xaa31b0ac,0x3b1639cf,0x2e2d3493,0xbbf1bb9c,0x3c003c00,0x3c003c00,0x3c003c00,0x3c003c00,
0x3b643c00,0x361f39a8,0xb61f0000,0xbb64b9a8,0x39a83c00,0xb9a80000,0xb9a8bc00,0x39a80000,0x361f3c00,0xbb64b9a8,0x3b640000,0xb61f39a8,
0x3c00,0xbc00,0x3c00,0xbc00,0xb61f3c00,0x3b64b9a8,0xbb640000,0x361f39a8,0xb9a83c00,0x39a80000,0x39a8bc00,0xb9a80000,
0xbb643c00,0xb61f39a8,0x361f0000,0x3b64b9a8,0x3c003c00,0x3c003c00,0x3c003c00,0x3c003c00,0xbb64bc00,0xb61fb9a8,0x361f0000,0x3b6439a8,
0x39a83c00,0xb9a80000,0xb9a8bc00,0x39a80000,0xb61fbc00,0x3b6439a8,0xbb640000,0x361fb9a8,0x3c00,0xbc00,0x3c00,0xbc00,
0x361fbc00,0xbb6439a8,0x3b640000,0xb61fb9a8,0xb9a83c00,0x39a80000,0x39a8bc00,0xb9a80000,0x3b64bc00,0x361fb9a8,0xb61f0000,0xbb6439a8,
0x0,0x0,0x0,0x0,0x361f0000,0x3b6439a8,0x3b643c00,0x361f39a8,0x39a80000,0x39a83c00,0xb9a80000,0xb9a8bc00,
0x3b640000,0xb61f39a8,0xb61fbc00,0x3b6439a8,0x3c000000,0xbc000000,0x3c000000,0xbc000000,0x3b640000,0xb61fb9a8,0xb61f3c00,0x3b64b9a8,
0x39a80000,0x39a8bc00,0xb9a80000,0xb9a83c00,0x361f0000,0x3b64b9a8,0x3b64bc00,0x361fb9a8,0x0,0x0,0x0,0x0,
0xb61f0000,0xbb64b9a8,0xbb64bc00,0xb61fb9a8,0x39a80000,0x39a83c00,0xb9a80000,0xb9a8bc00,0xbb640000,0x361fb9a8,0x361f3c00,0xbb64b9a8,
0x3c000000,0xbc000000,0x3c000000,0xbc000000,0xbb640000,0x361f39a8,0x361fbc00,0xbb6439a8,0x39a80000,0x39a8bc00,0xb9a80000,0xb9a83c00,
0xb61f0000,0xbb6439a8,0xbb643c00,0xb61f39a8,0xbc003c00,0xbc003c00,0xbc003c00,0xbc003c00,0xbb643c00,0xb61f39a8,0x361f0000,0x3b64b9a8,
0xb9a83c00,0x39a80000,0x39a8bc00,0xb9a80000,0xb61f3c00,0x3b64b9a8,0xbb640000,0x361f39a8,0x3c00,0xbc00,0x3c00,0xbc00,
0x361f3c00,0xbb64b9a8,0x3b640000,0xb61f39a8,0x39a83c00,0xb9a80000,0xb9a8bc00,0x39a80000,0x3b643c00,0x361f39a8,0xb61f0000,0xbb64b9a8,
0xbc003c00,0xbc003c00,0xbc003c00,0xbc003c00,0x3b64bc00,0x361fb9a8,0xb61f0000,0xbb6439a8,0xb9a83c00,0x39a80000,0x39a8bc00,0xb9a80000,
0x361fbc00,0xbb6439a8,0x3b640000,0xb61fb9a8,0x3c00,0xbc00,0x3c00,0xbc00,0xb61fbc00,0x3b6439a8,0xbb640000,0x361fb9a8,
0x39a83c00,0xb9a80000,0xb9a8bc00,0x39a80000,0xbb64bc00,0xb61fb9a8,0x361f0000,0x3b6439a8,0x0,0x0,0x0,0x0,
0xb61f0000,0xbb6439a8,0xbb643c00,0xb61f39a8,0xb9a80000,0xb9a83c00,0x39a80000,0x39a8bc00,0xbb640000,0x361f39a8,0x361fbc00,0xbb6439a8,
0xbc000000,0x3c000000,0xbc000000,0x3c000000,0xbb640000,0x361fb9a8,0x361f3c00,0xbb64b9a8,0xb9a80000,0xb9a8bc00,0x39a80000,0x39a83c00,
0xb61f0000,0xbb64b9a8,0xbb64bc00,0xb61fb9a8,0x0,0x0,0x0,0x0,0x361f0000,0x3b64b9a8,0x3b64bc00,0x361fb9a8,
0xb9a80000,0xb9a83c00,0x39a80000,0x39a8bc00,0x3b640000,0xb61fb9a8,0xb61f3c00,0x3b64b9a8,0xbc000000,0x3c000000,0xbc000000,0x3c000000,
0x3b640000,0xb61f39a8,0xb61fbc00,0x3b6439a8,0xb9a80000,0xb9a8bc00,0x39a80000,0x39a83c00,0x361f0000,0x3b6439a8,0x3b643c00,0x361f39a8,
0x0,0x0,0x0,0x0,0xb61f0000,0xbb64b9a8,0xbb64bc00,0xb61fb9a8,0xb9a80000,0xb9a8bc00,0x39a80000,0x39a83c00,
0xbb640000,0x361fb9a8,0x361f3c00,0xbb64b9a8,0xbc000000,0x3c000000,0xbc000000,0x3c000000,0xbb640000,0x361f39a8,0x361fbc00,0xbb6439a8,
0xb9a80000,0xb9a83c00,0x39a80000,0x39a8bc00,0xb61f0000,0xbb6439a8,0xbb643c00,0xb61f39a8,0x0,0x0,0x0,0x0,
0x361f0000,0x3b6439a8,0x3b643c00,0x361f39a8,0xb9a80000,0xb9a8bc00,0x39a80000,0x39a83c00,0x3b640000,0xb61f39a8,0xb61fbc00,0x3b6439a8,
0xbc000000,0x3c000000,0xbc000000,0x3c000000,0x3b640000,0xb61fb9a8,0xb61f3c00,0x3b64b9a8,0xb9a80000,0xb9a83c00,0x39a80000,0x39a8bc00,
0x361f0000,0x3b64b9a8,0x3b64bc00,0x361fb9a8,0x3c003c00,0x3c003c00,0x3c003c00,0x3c003c00,0x3b643c00,0x361f39a8,0xb61f0000,0xbb64b9a8,
0x39a83c00,0xb9a80000,0xb9a8bc00,0x39a80000,0x361f3c00,0xbb64b9a8,0x3b640000,0xb61f39a8,0x3c00,0xbc00,0x3c00,0xbc00,
0xb61f3c00,0x3b64b9a8,0xbb640000,0x361f39a8,0xb9a83c00,0x39a80000,0x39a8bc00,0xb9a80000,0xbb643c00,0xb61f39a8,0x361f0000,0x3b64b9a8,
0x3c003c00,0x3c003c00,0x3c003c00,0x3c003c00,0xbb64bc00,0xb61fb9a8,0x361f0000,0x3b6439a8,0x39a83c00,0xb9a80000,0xb9a8bc00,0x39a80000,
0xb61fbc00,0x3b6439a8,0xbb640000,0x361fb9a8,0x3c00,0xbc00,0x3c00,0xbc00,0x361fbc00,0xbb6439a8,0x3b640000,0xb61fb9a8,
0xb9a83c00,0x39a80000,0x39a8bc00,0xb9a80000,0x3b64bc00,0x361fb9a8,0xb61f0000,0xbb6439a8,0x0,0x0,0x0,0x0,
0x361f0000,0x3b64b9a8,0x3b64bc00,0x361fb9a8,0x39a80000,0x39a8bc00,0xb9a80000,0xb9a83c00,0x3b640000,0xb61fb9a8,0xb61f3c00,0x3b64b9a8,
0x3c000000,0xbc000000,0x3c000000,0xbc000000,0x3b640000,0xb61f39a8,0xb61fbc00,0x3b6439a8,0x39a80000,0x39a83c00,0xb9a80000,0xb9a8bc00,
0x361f0000,0x3b6439a8,0x3b643c00,0x361f39a8,0x0,0x0,0x0,0x0,0xb61f0000,0xbb6439a8,0xbb643c00,0xb61f39a8,
0x39a80000,0x39a8bc00,0xb9a80000,0xb9a83c00,0xbb640000,0x361f39a8,0x361fbc00,0xbb6439a8,0x3c000000,0xbc000000,0x3c000000,0xbc000000,
0xbb640000,0x361fb9a8,0x361f3c00,0xbb64b9a8,0x39a80000,0x39a83c00,0xb9a80000,0xb9a8bc00,0xb61f0000,0xbb64b9a8,0xbb64bc00,0xb61fb9a8,
0xbc003c00,0xbc003c00,0xbc003c00,0xbc003c00,0xbb643c00,0xb61f39a8,0x361f0000,0x3b64b9a8,0xb9a83c00,0x39a80000,0x39a8bc00,0xb9a80000,
0xb61f3c00,0x3b64b9a8,0xbb640000,0x361f39a8,0x3c00,0xbc00,0x3c00,0xbc00,0x361f3c00,0xbb64b9a8,0x3b640000,0xb61f39a8,
0x39a83c00,0xb9a80000,0xb9a8bc00,0x39a80000,0x3b643c00,0x361f39a8,0xb61f0000,0xbb64b9a8,0xbc003c00,0xbc003c00,0xbc003c00,0xbc003c00,
0x3b64bc00,0x361fb9a8,0xb61f0000,0xbb6439a8,0xb9a83c00,0x39a80000,0x39a8bc00,0xb9a80000,0x361fbc00,0xbb6439a8,0x3b640000,0xb61fb9a8,
0x3c00,0xbc00,0x3c00,0xbc00,0xb61fbc00,0x3b6439a8,0xbb640000,0x361fb9a8,0x39a83c00,0xb9a80000,0xb9a8bc00,0x39a80000,
0xbb64bc00,0xb61fb9a8,0x361f0000,0x3b6439a8};

__device__ unsigned int g_gate_part[NCL * S_LEN];
__device__ unsigned int g_epoch[NCL * CLS];
#define TS(e)
#define TG(e)
#define TSW(e)
#define TS_DUMP()

__device__ __forceinline__ void wg_fence() { asm volatile("wgmma.fence.sync.aligned;" ::: "memory"); }
__device__ __forceinline__ void wg_commit() { asm volatile("wgmma.commit_group.sync.aligned;" ::: "memory"); }
template <int N> __device__ __forceinline__ void wg_wait() { asm volatile("wgmma.wait_group.sync.aligned %0;" ::"n"(N) : "memory"); }
__device__ __forceinline__ void fence_async() { asm volatile("fence.proxy.async.shared::cta;" ::: "memory"); }
__device__ __forceinline__ void bar_sync(int id, int n) { asm volatile("bar.sync %0, %1;" ::"r"(id), "r"(n) : "memory"); }
__device__ __forceinline__ void bar_arrive(int id, int n) { asm volatile("bar.arrive %0, %1;" ::"r"(id), "r"(n) : "memory"); }
__device__ __forceinline__ uint32_t lds16(uint32_t a) { unsigned short v; asm volatile("ld.shared.b16 %0, [%1];" : "=h"(v) : "r"(a)); return v; }
__device__ __forceinline__ uint32_t lds32(uint32_t a) { uint32_t v; asm volatile("ld.shared.b32 %0, [%1];" : "=r"(v) : "r"(a)); return v; }
__device__ __forceinline__ void lds32p(uint32_t& v, uint32_t a, int p) { asm volatile("{\n.reg .pred q;\nsetp.ne.b32 q, %2, 0;\n@q ld.shared.b32 %0, [%1];\n}\n" : "+r"(v) : "r"(a), "r"(p)); }
__device__ __forceinline__ uint2 lds64(uint32_t a) { uint2 v; asm volatile("ld.shared.v2.b32 {%0,%1}, [%2];" : "=r"(v.x), "=r"(v.y) : "r"(a)); return v; }
__device__ __forceinline__ uint4 lds128(uint32_t a) { uint4 v; asm volatile("ld.shared.v4.b32 {%0,%1,%2,%3}, [%4];" : "=r"(v.x), "=r"(v.y), "=r"(v.z), "=r"(v.w) : "r"(a)); return v; }
__device__ __forceinline__ void sts32(uint32_t a, uint32_t v) { asm volatile("st.shared.b32 [%0], %1;" ::"r"(a), "r"(v) : "memory"); }
__device__ __forceinline__ void sts16(uint32_t a, uint32_t v) { asm volatile("st.shared.b16 [%0], %1;" ::"r"(a), "h"((unsigned short)v) : "memory"); }
__device__ __forceinline__ void sts128(uint32_t a, uint32_t x, uint32_t y, uint32_t z, uint32_t w) { asm volatile("st.shared.v4.b32 [%0], {%1,%2,%3,%4};" ::"r"(a), "r"(x), "r"(y), "r"(z), "r"(w) : "memory"); }
__device__ __forceinline__ void ldsm4(uint32_t (&r)[4], uint32_t a) { asm volatile("ldmatrix.sync.aligned.m8n8.x4.shared.b16 {%0,%1,%2,%3}, [%4];" : "=r"(r[0]), "=r"(r[1]), "=r"(r[2]), "=r"(r[3]) : "r"(a)); }
__device__ __forceinline__ void ldsm4t(uint32_t (&r)[4], uint32_t a) { asm volatile("ldmatrix.sync.aligned.m8n8.x4.trans.shared.b16 {%0,%1,%2,%3}, [%4];" : "=r"(r[0]), "=r"(r[1]), "=r"(r[2]), "=r"(r[3]) : "r"(a)); }
__device__ __forceinline__ void ldsm2t(uint32_t& r0, uint32_t& r1, uint32_t a) { asm volatile("ldmatrix.sync.aligned.m8n8.x2.trans.shared.b16 {%0,%1}, [%2];" : "=r"(r0), "=r"(r1) : "r"(a)); }
__device__ __forceinline__ void stsm4t(uint32_t a, uint32_t r0, uint32_t r1, uint32_t r2, uint32_t r3) { asm volatile("stmatrix.sync.aligned.m8n8.x4.trans.shared.b16 [%0], {%1,%2,%3,%4};" ::"r"(a), "r"(r0), "r"(r1), "r"(r2), "r"(r3) : "memory"); }
__device__ __forceinline__ void stsm4(uint32_t a, const uint32_t (&r)[4]) { asm volatile("stmatrix.sync.aligned.m8n8.x4.shared.b16 [%0], {%1,%2,%3,%4};" ::"r"(a), "r"(r[0]), "r"(r[1]), "r"(r[2]), "r"(r[3]) : "memory"); }
__device__ __forceinline__ void tma_store(const CUtensorMap* m, uint32_t src, int c0, int c1) {
  asm volatile("cp.async.bulk.tensor.2d.global.shared::cta.bulk_group [%0, {%2, %3}], [%1];" ::"l"(m), "r"(src), "r"(c0), "r"(c1) : "memory");
}
__device__ __forceinline__ uint32_t mapa(uint32_t a, uint32_t rank) { uint32_t r; asm("mapa.shared::cluster.u32 %0, %1, %2;" : "=r"(r) : "r"(a), "r"(rank)); return r; }
__device__ __forceinline__ void st_async4(uint32_t a, uint32_t x, uint32_t y, uint32_t z, uint32_t w, uint32_t mbar) {
  asm volatile("st.async.weak.shared::cluster.mbarrier::complete_tx::bytes.v4.b32 [%0], {%1,%2,%3,%4}, [%5];" ::"r"(a), "r"(x), "r"(y), "r"(z), "r"(w), "r"(mbar) : "memory");
}
__device__ __forceinline__ bool elect() {
  uint32_t p;
  asm volatile("{\n.reg .pred p;\nelect.sync _|p, 0xffffffff;\nselp.u32 %0, 1, 0, p;\n}\n" : "=r"(p));
  return p;
}
template <int N = 512> __device__ __forceinline__ void bulk_send(uint32_t dst, uint32_t src, uint32_t mbar) {
  asm volatile("cp.async.bulk.shared::cluster.shared::cta.mbarrier::complete_tx::bytes [%0], [%1], %3, [%2];" ::"r"(dst), "r"(src), "r"(mbar), "n"(N) : "memory");
}
__device__ __forceinline__ void st_async1(uint32_t a, uint32_t x, uint32_t mbar) {
  asm volatile("st.async.weak.shared::cluster.mbarrier::complete_tx::bytes.b32 [%0], %1, [%2];" ::"r"(a), "r"(x), "r"(mbar) : "memory");
}
__device__ __forceinline__ void mbar_init(uint32_t b, uint32_t n) { asm volatile("mbarrier.init.shared::cta.b64 [%0], %1;" ::"r"(b), "r"(n) : "memory"); }
__device__ __forceinline__ void mbar_expect(uint32_t b, uint32_t bytes) { asm volatile("mbarrier.arrive.expect_tx.shared::cta.b64 _, [%0], %1;" ::"r"(b), "r"(bytes) : "memory"); }
__device__ __forceinline__ void mbar_arrive(uint32_t b) { asm volatile("mbarrier.arrive.shared::cta.b64 _, [%0];" ::"r"(b) : "memory"); }
__device__ __forceinline__ void mbar_wait(uint32_t b) {
  asm volatile("{\n.reg .pred p;\n.reg .u32 n;\nmov.u32 n, 0;\nWAIT_LOOP:\nmbarrier.try_wait.parity.shared::cta.b64 p, [%0], 0;\n"
               "add.u32 n, n, 1;\nsetp.gt.or.u32 p, n, 4000000, p;\n@!p bra WAIT_LOOP;\n}\n" ::"r"(b) : "memory");
}
__device__ __forceinline__ void tma4(uint32_t dst, const CUtensorMap* m, int c0, int c3, uint32_t mbar) {
  asm volatile("cp.async.bulk.tensor.4d.shared::cluster.global.mbarrier::complete_tx::bytes [%0], [%1, {%3, %4, %4, %5}], [%2];" ::"r"(dst), "l"(m), "r"(mbar), "r"(c0), "r"(0), "r"(c3) : "memory");
}
__device__ __forceinline__ uint32_t prmt(uint32_t a, uint32_t b, uint32_t s) { uint32_t r; asm("prmt.b32 %0, %1, %2, %3;" : "=r"(r) : "r"(a), "r"(b), "r"(s)); return r; }
__device__ __forceinline__ uint32_t hmul(uint32_t a, uint32_t b) { uint32_t r; asm("mul.rn.bf16x2 %0, %1, %2;" : "=r"(r) : "r"(a), "r"(b)); return r; }
__device__ __forceinline__ uint32_t hadd(uint32_t a, uint32_t b) { uint32_t r; asm("add.rn.bf16x2 %0, %1, %2;" : "=r"(r) : "r"(a), "r"(b)); return r; }
__device__ __forceinline__ uint32_t hfma(uint32_t a, uint32_t b, uint32_t c) { uint32_t r; asm("fma.rn.bf16x2 %0, %1, %2, %3;" : "=r"(r) : "r"(a), "r"(b), "r"(c)); return r; }
__device__ __forceinline__ void mma16(float (&d)[4], const uint32_t (&a)[4], uint32_t b0, uint32_t b1) {
  asm volatile("mma.sync.aligned.m16n8k16.row.col.f32.bf16.bf16.f32 {%0,%1,%2,%3}, {%4,%5,%6,%7}, {%8,%9}, {%0,%1,%2,%3};"
               : "+f"(d[0]), "+f"(d[1]), "+f"(d[2]), "+f"(d[3]) : "r"(a[0]), "r"(a[1]), "r"(a[2]), "r"(a[3]), "r"(b0), "r"(b1));
}
__device__ __forceinline__ void rowsum16(float (&d)[4], const uint32_t (&a)[4], uint32_t w0, uint32_t w1) {
  const uint32_t p[4] = {hmul(a[0], w0), hmul(a[1], w0), hmul(a[2], w1), hmul(a[3], w1)};
  mma16(d, p, 0x3f803f80u, 0x3f803f80u);
}
__device__ __forceinline__ void mma8(float (&d)[4], uint32_t a0, uint32_t a1, uint32_t b0) {
  asm volatile("mma.sync.aligned.m16n8k8.row.col.f32.bf16.bf16.f32 {%0,%1,%2,%3}, {%4,%5}, {%6}, {%0,%1,%2,%3};"
               : "+f"(d[0]), "+f"(d[1]), "+f"(d[2]), "+f"(d[3]) : "r"(a0), "r"(a1), "r"(b0));
}
__device__ __forceinline__ uint32_t pack_bf(float lo, float hi) { uint32_t r; asm("cvt.rn.bf16x2.f32 %0, %1, %2;" : "=r"(r) : "f"(hi), "f"(lo)); return r; }
__device__ __forceinline__ __half2 pack_h(float lo, float hi) { return __floats2half2_rn(lo, hi); }
__device__ __forceinline__ float bf_lo(uint32_t v) { return __uint_as_float(v << 16); }
__device__ __forceinline__ float rbf(float x) { return bf_lo(pack_bf(x, 0.f)); }

struct Params {
  const bf16* s4[4];
  const bf16 *shift_k, *ssm_D, *ldt, *dskip, *gate_w;
  const uint32_t* dft;
  unsigned int *gate_part, *epoch;
  int gate_at;
};

struct cplx { float r, i; };
__device__ __forceinline__ cplx cmul(cplx a, cplx b) { cplx c; c.r = fmaf(a.r, b.r, -a.i * b.i); c.i = fmaf(a.r, b.i, a.i * b.r); return c; }
__device__ __forceinline__ cplx csqr(cplx a) { cplx c; c.r = fmaf(a.r, a.r, -a.i * a.i); c.i = (a.r + a.r) * a.i; return c; }
__device__ __forceinline__ cplx cexp_p(float ar, float ai, float p) {
  float m; asm("ex2.approx.ftz.f32 %0, %1;" : "=f"(m) : "f"(ar * (p * 1.4426950408889634f)));
  const float ph = ai * p;
  cplx c; c.r = m * __cosf(ph); c.i = m * __sinf(ph); return c;
}
struct hv { __half2 r, i; };
__device__ __forceinline__ hv hcmul(hv x, __half2 e) {
  const __half2 er = __low2half2(e), ei = __high2half2(e);
  hv y; y.r = __hfma2(x.r, er, __hneg2(__hmul2(x.i, ei))); y.i = __hfma2(x.r, ei, __hmul2(x.i, er)); return y;
}
__device__ __forceinline__ uint32_t h2u(__half2 h) { return *reinterpret_cast<uint32_t*>(&h); }
__device__ __forceinline__ hv lows(hv a, hv b) { hv y; y.r = __lows2half2(a.r, b.r); y.i = __lows2half2(a.i, b.i); return y; }
__device__ __forceinline__ void put_group(uint32_t a, const hv& v0, const hv& v1, const hv& v2, const hv& v3) {
  sts128(a, h2u(v0.r), h2u(v1.r), h2u(v2.r), h2u(v3.r));
  sts128(a + 256, h2u(v0.i), h2u(v1.i), h2u(v2.i), h2u(v3.i));
}
struct KSetup { hv v0, x0; __half2 e2, e4, e16, e32, e64, e128, e256, e512, e1k; };
__device__ __forceinline__ KSetup ksetup(uint32_t par, int n) {
  const uint32_t pn = par + 2 * n;
  const uint4 sc = lds128(par + 1024);
  const float dt = __uint_as_float(sc.x), sdn = __uint_as_float(sc.z);
  const float ar = -rbf(expf(bf_lo(lds16(pn)))) * dt;
  const float ai = bf_lo(lds16(pn + 256)) * dt;
  cplx C; C.r = bf_lo(lds16(pn + 512)) * sdn; C.i = bf_lo(lds16(pn + 768)) * sdn;
  const cplx E1 = cexp_p(ar, ai, 1.f), E64 = cexp_p(ar, ai, 64.f);
  const cplx E2 = csqr(E1), E4 = csqr(E2), E8 = csqr(E4), E16 = csqr(E8), E32 = csqr(E16);
  const cplx E128 = csqr(E64), E256 = csqr(E128), E512 = csqr(E256), E1k = csqr(E512);
  const cplx C1 = cmul(C, E1);
  KSetup s;
  s.v0.r = pack_h(1.f, E8.r); s.v0.i = pack_h(0.f, E8.i);
  s.x0.r = pack_h(C.r, C1.r); s.x0.i = pack_h(C.i, C1.i);
  s.e2 = pack_h(E2.r, E2.i); s.e4 = pack_h(E4.r, E4.i); s.e16 = pack_h(E16.r, E16.i); s.e32 = pack_h(E32.r, E32.i);
  s.e64 = pack_h(E64.r, E64.i); s.e128 = pack_h(E128.r, E128.i); s.e256 = pack_h(E256.r, E256.i); s.e512 = pack_h(E512.r, E512.i);
  s.e1k = pack_h(E1k.r, E1k.i);
  return s;
}
__device__ __forceinline__ void kstage(const KSetup& s, uint32_t sb, uint32_t sn) {
  hv v[8], z[4];
  v[0] = s.v0;
  v[1] = hcmul(v[0], s.e16);
  v[2] = hcmul(v[0], s.e32); v[3] = hcmul(v[1], s.e32);
#pragma unroll
  for (int i = 0; i < 4; i++) v[4 + i] = hcmul(v[i], s.e64);
#pragma unroll
  for (int i = 0; i < 4; i++) z[i] = hcmul(v[i], s.e128);
  put_group(sb + 4096, z[0], z[1], z[2], z[3]);
  put_group(sb, v[0], v[1], v[2], v[3]);
#pragma unroll
  for (int i = 0; i < 4; i++) z[i] = hcmul(v[4 + i], s.e128);
  put_group(sb + 6144, z[0], z[1], z[2], z[3]);
  put_group(sb + 2048, v[4], v[5], v[6], v[7]);
  const hv x0 = s.x0, x1 = hcmul(x0, s.e2), x2 = hcmul(x0, s.e4), x3 = hcmul(x1, s.e4);
  const hv y0 = hcmul(lows(x0, x1), s.e256), y1 = hcmul(lows(x2, x3), s.e256);
  const hv y2 = hcmul(lows(x0, x2), s.e512), y3 = hcmul(lows(y0, y1), s.e512);
  const hv z0 = hcmul(lows(x0, y0), s.e1k), z1 = hcmul(lows(y2, y3), s.e1k), z2 = hcmul(z0, s.e1k);
  put_group(sn, x0, x1, x2, x3);
  put_group(sn + 2048, y0, y1, y2, y3);
  put_group(sn + 4096, z0, z1, z2, z2);
}
template <int KS> __device__ __forceinline__ void kmma(float (&d)[24], uint64_t da) {
  if constexpr (KS < 8) {
    const uint64_t a = da + (uint64_t)(KS * 16);
    asm volatile("{\n.reg .pred p;\nsetp.ne.b32 p, %26, 0;\n"
                 "wgmma.mma_async.sync.aligned.m64n48k16.f32.f16.f16 {%0,%1,%2,%3,%4,%5,%6,%7,%8,%9,%10,%11,%12,%13,%14,%15,%16,%17,%18,%19,%20,%21,%22,%23}, %24, %25, p, %27, 1, 1, 1;\n}\n"
                 : "+f"(d[0]), "+f"(d[1]), "+f"(d[2]), "+f"(d[3]), "+f"(d[4]), "+f"(d[5]), "+f"(d[6]), "+f"(d[7]), "+f"(d[8]), "+f"(d[9]), "+f"(d[10]), "+f"(d[11]), "+f"(d[12]), "+f"(d[13]), "+f"(d[14]), "+f"(d[15]), "+f"(d[16]), "+f"(d[17]), "+f"(d[18]), "+f"(d[19]), "+f"(d[20]), "+f"(d[21]), "+f"(d[22]), "+f"(d[23])
                 : "l"(a), "l"(a + 1024), "r"(KS > 0 ? 1 : 0), "n"((KS & 1) ? -1 : 1));
    kmma<KS + 1>(d, da);
  }
}
__device__ __forceinline__ void kcompact(const float* d, uint32_t a0, uint32_t a1, uint32_t a1h, uint32_t a2, bool lo, bool top) {
  sts32(a0, pack_bf(d[0], d[1]));
  sts32(a0 + 128, pack_bf(d[2], d[3]));
  sts32(a1, pack_bf(d[4], d[5]));
  sts32(a1h, pack_bf(d[6], d[7]));
  const uint32_t p0 = pack_bf(d[8], d[9]), p1 = pack_bf(d[10], d[11]);
  if (lo || top) sts16(a2, p0);
  if (lo) { sts16(a2 + 64, p0 >> 16); sts16(a2 + 16, p1); sts16(a2 + 80, p1 >> 16); }
}
__device__ __forceinline__ uint32_t cmp32(uint32_t a) { return hadd(lds32(a), lds32(a + CMP_H)); }

#define WG64F(NAME, TY) \
__device__ __forceinline__ void NAME(float (&d)[32], const uint32_t* a, uint64_t desc, int sc) { \
  asm volatile("{\n.reg .pred p;\nsetp.ne.b32 p, %37, 0;\n" \
    "wgmma.mma_async.sync.aligned.m64n64k16.f32." TY "." TY " {%0,%1,%2,%3,%4,%5,%6,%7,%8,%9,%10,%11,%12,%13,%14,%15,%16,%17,%18,%19,%20,%21,%22,%23,%24,%25,%26,%27,%28,%29,%30,%31}, {%32,%33,%34,%35}, %36, p, 1, 1, 1;\n}\n" \
    : "+f"(d[0]),"+f"(d[1]),"+f"(d[2]),"+f"(d[3]),"+f"(d[4]),"+f"(d[5]),"+f"(d[6]),"+f"(d[7]),"+f"(d[8]),"+f"(d[9]),"+f"(d[10]),"+f"(d[11]),"+f"(d[12]),"+f"(d[13]),"+f"(d[14]),"+f"(d[15]),"+f"(d[16]),"+f"(d[17]),"+f"(d[18]),"+f"(d[19]),"+f"(d[20]),"+f"(d[21]),"+f"(d[22]),"+f"(d[23]),"+f"(d[24]),"+f"(d[25]),"+f"(d[26]),"+f"(d[27]),"+f"(d[28]),"+f"(d[29]),"+f"(d[30]),"+f"(d[31]) \
    : "r"(a[0]), "r"(a[1]), "r"(a[2]), "r"(a[3]), "l"(desc), "r"(sc)); \
}
WG64F(wg64b, "bf16")
WG64F(wg64f, "f16")
template <int SA> __device__ __forceinline__ void wg32h(uint32_t* d, const uint32_t* a, uint64_t desc, int sc) {
  asm volatile("{\n.reg .pred p;\nsetp.ne.b32 p, %13, 0;\n"
    "wgmma.mma_async.sync.aligned.m64n32k16.f16.f16.f16 {%0,%1,%2,%3,%4,%5,%6,%7}, {%8,%9,%10,%11}, %12, p, %14, 1, 0;\n}\n"
    : "+r"(d[0]),"+r"(d[1]),"+r"(d[2]),"+r"(d[3]),"+r"(d[4]),"+r"(d[5]),"+r"(d[6]),"+r"(d[7])
    : "r"(a[0]), "r"(a[1]), "r"(a[2]), "r"(a[3]), "l"(desc), "r"(sc), "n"(SA));
}
struct Consts { uint32_t f1[8], gm[16], tr[2], ti[2], fe; };
__device__ __forceinline__ __half2 u2h(uint32_t u) { return *reinterpret_cast<__half2*>(&u); }
__device__ __forceinline__ void twid(uint32_t& ro, uint32_t& io, __half2 R, __half2 I, const Consts& K, int jj) {
  const __half2 x = __hfma2(I, u2h(K.tr[jj]), R), y = __hfma2(x, u2h(K.ti[jj]), I);
  ro = h2u(__hfma2(y, u2h(K.tr[jj]), x)); io = h2u(y);
}
#define IX(s, jj) (8 * ((s) >> 1) + 2 * (jj) + ((s) & 1))
template <int CJ> __device__ __forceinline__ void dft16(uint32_t (&d)[16], const uint32_t (&a)[16], uint64_t db2) {
  wg32h<1>(d, a, db2, 0); wg32h<1>(d + 8, a + 8, db2, 0); wg32h<CJ ? -1 : 1>(d, a + 4, db2 + 16, 1); wg32h<CJ ? -1 : 1>(d + 8, a + 12, db2 + 16, 1);
  wg_commit();
}
__device__ __forceinline__ void twid_fwd(uint32_t (&a)[16], const float (&d)[32], const Consts& K) {
#pragma unroll
  for (int j = 0; j < 8; j++) twid(a[IX(j >> 1, j & 1)], a[IX(j >> 1, j & 1) + 4], pack_h(d[4 * j], d[4 * j + 1]), pack_h(d[4 * j + 2], d[4 * j + 3]), K, j & 1);
}
__device__ __forceinline__ uint64_t mkdesc(uint32_t lo, uint32_t hi) { return (uint64_t)lo | ((uint64_t)hi << 32); }
__device__ __forceinline__ uint32_t amax(uint32_t a, uint32_t b) { uint32_t r; asm("max.xorsign.abs.bf16x2 %0, %1, %2;" : "=r"(r) : "r"(a), "r"(b)); return r; }
__device__ __forceinline__ uint32_t amax8(uint32_t a) {
  const uint4 x = lds128(a), z = lds128(a + 2048);
  return amax(amax(amax(x.x, x.y), amax(x.z, x.w)), amax(amax(z.x, z.y), amax(z.z, z.w)));
}
__device__ __forceinline__ uint32_t fft_conv(float (&dy)[32], Consts& K, uint32_t smt, uint32_t sm16, uint32_t so, uint32_t to, uint32_t mx,
                                                            uint32_t vo, uint32_t va, int barid) {
  fence_async();
  const uint32_t mu = amax8(smt + so), mk = amax8(smt + to);
  const uint32_t m = amax(prmt(mu, mk, 0x5410), prmt(mu, mk, 0x7632));
  const uint32_t wu = __reduce_max_sync(0xffffffffu, m & 0x7f80u), wk = __reduce_max_sync(0xffffffffu, m & 0x7f800000u);
  sts32(mx, wu | wk);
  bar_sync(barid, 128);
  const uint4 mm = lds128(mx & ~15u);
  const uint32_t e2 = __vminu2(__vmaxu2(__vmaxu2(__vmaxu2(mm.x, mm.y), mm.z), __vmaxu2(mm.w, 0x20002000u)), 0x5e805e80u);
  const uint32_t eu = prmt(e2, 0, 0x1010), ek = prmt(e2, 0, 0x3232);
  const uint32_t su = K.fe - eu, sk = K.fe - ek, sy = eu + ek - 0x40004000u;
  K.fe = eu;
  const uint64_t db2 = mkdesc(sm16 + B2 / 16 + (8 << 16), 32);
  uint32_t az[16];
  {
    uint32_t du[16], dk[16], au[16], ak[16];
    {
      float d1u[32], d1k[32];
      uint32_t fk[8];
      uint32_t* fu = K.f1;
#pragma unroll
      for (int i = 0; i < 8; i++) { fk[i] = K.f1[i] + sk; K.f1[i] += su; asm volatile("" : "+r"(K.f1[i]), "+r"(fk[i])); }
      const uint64_t ds = mkdesc(sm16 + (64 << 16) + so / 16, 0xc0000010u), dt = mkdesc(sm16 + (64 << 16) + to / 16, 0xc0000010u);
      wg_fence();
      wg64b(d1u, fu, ds, 0); wg64b(d1u, fu + 4, ds + 32, 1); wg_commit();
      wg64b(d1k, fk, dt, 0); wg64b(d1k, fk + 4, dt + 32, 1); wg_commit();
      wg_wait<1>();
      twid_fwd(au, d1u, K);
      wg_fence(); dft16<0>(du, au, db2);
      wg_wait<1>();
      twid_fwd(ak, d1k, K);
      wg_fence(); dft16<0>(dk, ak, db2);
      wg_wait<0>();
    }
#pragma unroll
    for (int jj = 0; jj < 2; jj++)
#pragma unroll
      for (int j = 0; j < 4; j++) {
        __half2 n = __hmul2(u2h(du[IX(0, jj) + 4]), u2h(dk[IX(j, jj) + 4])), zi = __hmul2(u2h(du[IX(0, jj) + 4]), u2h(dk[IX(j, jj)]));
#pragma unroll
        for (int a = 1; a <= j; a++) { n = __hfma2(u2h(du[IX(a, jj) + 4]), u2h(dk[IX(j - a, jj) + 4]), n); zi = __hfma2(u2h(du[IX(a, jj) + 4]), u2h(dk[IX(j - a, jj)]), zi); }
        __half2 zr = __hneg2(n);
#pragma unroll
        for (int a = 0; a <= j; a++) { zr = __hfma2(u2h(du[IX(a, jj)]), u2h(dk[IX(j - a, jj)]), zr); zi = __hfma2(u2h(du[IX(a, jj)]), u2h(dk[IX(j - a, jj) + 4]), zi); }
        az[IX(j, jj)] = h2u(zr); az[IX(j, jj) + 4] = h2u(zi);
      }
  }
  {
    uint32_t dz[16];
    wg_fence(); dft16<1>(dz, az, db2);
    wg_wait<0>();
#pragma unroll
    for (int s = 0; s < 2; s++) {
      uint32_t vr[4], vi[4];
#pragma unroll
      for (int m = 0; m < 4; m++) {
        vr[m] = h2u(__hfma2(u2h(dz[8 * s + 4 + m]), u2h(K.tr[m >> 1]), u2h(dz[8 * s + m])));
        vi[m] = h2u(__hfma2(u2h(vr[m]), u2h(K.ti[m >> 1]), u2h(dz[8 * s + 4 + m])));
      }
      asm volatile("stmatrix.sync.aligned.m8n8.x4.shared.b16 [%4], {%0,%1,%2,%3};" : "+r"(vi[0]), "+r"(vi[1]), "+r"(vi[2]), "+r"(vi[3]) : "r"(va + 4096 * s + 128) : "memory");
#pragma unroll
      for (int m = 0; m < 4; m++) vr[m] = h2u(__hfma2(u2h(vi[m]), u2h(K.tr[m >> 1]), u2h(vr[m])));
      stsm4(va + 4096 * s, vr);
    }
  }
  fence_async();
  bar_sync(barid, 128);
  const uint64_t dv = mkdesc(sm16 + vo / 16 + (8 << 16), 64);
  wg_fence();
#pragma unroll
  for (int ks = 0; ks < 4; ks++) wg64f(dy, K.gm + 4 * ks, dv + 16 * ks, ks > 0);
  wg_commit();
  return sy;
}
__device__ __forceinline__ void fft_finish(uint32_t (&y)[8], float (&dy)[32], uint32_t sy) {
  wg_wait<0>();
#pragma unroll
  for (int j = 0; j < 8; j++) y[j] = hmul(j < 2 ? pack_bf(dy[4 * j], dy[4 * j + 1]) : pack_bf(dy[4 * j] + dy[4 * j - 6], dy[4 * j + 1] + dy[4 * j - 5]), sy);
}

__global__ void __cluster_dims__(CLS, 1, 1) __launch_bounds__(512, 1)
fused_kernel(const __grid_constant__ CUtensorMap mq, const __grid_constant__ CUtensorMap mk, const __grid_constant__ CUtensorMap mv, const __grid_constant__ CUtensorMap mt,
             const __grid_constant__ CUtensorMap mo8, const __grid_constant__ CUtensorMap mo16, const __grid_constant__ Params P) {
  extern __shared__ __align__(1024) uint8_t smem[];
  const uint32_t sm = (uint32_t)__cvta_generic_to_shared(smem);
  const int tid = threadIdx.x, lane = tid & 31;
  const int cl = blockIdx.x >> 3, rank = blockIdx.x & 7;
  const int ch0 = min(cl * RMAX * 8, D_CH - RMAX * 8);
  const uint32_t gomap = (ch0 & 8) ? 0x42310u : 0x31204u;
#define GO(r) ((gomap >> (4 * (r))) & 7)
  const uint32_t bars = sm + BARS;
  TS((tid >> 7) * 32 + 0); TG(126);
  const int wid = __shfl_sync(0xffffffffu, tid >> 5, 0);
  const int wg = wid >> 2, w = wid & 3, t = tid & 127;
  const int g = lane >> 2, c = lane & 3, lm = lane >> 3, lj = lane & 7;

  uint4 pv = make_uint4(0, 0, 0, 0);
  if (wg == 3) {
    if (w < 2) { if (w == 0) {
      if (elect()) {
#pragma unroll
        for (int i = 0; i < B_KV; i++) mbar_init(bars + 8 * i, 1);
        asm volatile("fence.mbarrier_init.release.cluster;" ::: "memory");
#pragma unroll
        for (int i = 0; i < 2; i++) { mbar_expect(bars + 8 * (B_Q + i), 128 * PITCH + 2048 * i); tma4(sm + RAWQ + i * 128 * PITCH, &mq, ch0, rank * 8 + 4 * i, bars + 8 * (B_Q + i)); }
        asm volatile("cp.async.bulk.shared::cluster.global.mbarrier::complete_tx::bytes [%0], [%1], 2048, [%2];" ::"r"(sm + B2), "l"(P.dft + 3584), "r"(bars + 8 * (B_Q + 1)) : "memory");
      }
    } else {
      if (elect()) {
#pragma unroll
        for (int i = B_KV; i < B_END; i++) mbar_init(bars + 8 * i, i >= B_Y ? 128 : i >= B_O ? 3 : i >= B_U + 5 ? 2 : i >= B_U + 3 ? 129 : 1);
        asm volatile("fence.mbarrier_init.release.cluster;" ::: "memory");
        asm volatile("prefetch.tensormap [%0];" ::"l"(&mk) : "memory");
        asm volatile("prefetch.tensormap [%0];" ::"l"(&mv) : "memory");
      }
      __syncwarp();
      if (lane >= B_KV && lane < B_Y) mbar_expect(bars + 8 * lane, lane == B_KV ? (256 + 288) * PITCH : lane == B_T ? RMAX * 4096 : lane < B_G ? 4096 : 7 * 512);
    } } else if (tid < 480) {
      const uint4* src = lane < 8 ? (const uint4*)(P.gate_w + ch0) + lane : (const uint4*)(P.shift_k + ch0 * 4) + (lane - 8);
      if ((lane < RMAX && ch0 + 8 * lane >= cl * RMAX * 8) || (lane >= 8 && lane < 8 + 4 * RMAX)) pv = __ldg(src);
    } else {
      const int ch = ch0 + 8 * GO(min(lane, RMAX - 1)) + rank;
      pv.x = __ldg((const unsigned short*)P.ldt + ch); pv.y = __ldg((const unsigned short*)P.ssm_D + ch); pv.z = __ldg((const unsigned short*)P.dskip + ch);
      pv.w = __ldcg(P.epoch + blockIdx.x);
    }
    __syncwarp();
  } else if (tid < 320) {
    pv = __ldg((const uint4*)(P.s4[(tid >> 4) & 3] + (ch0 + 8 * GO(tid >> 6) + rank) * NST) + (tid & 15));
  }
  Consts K;
  {
    uint32_t* kr = (uint32_t*)&K;
#pragma unroll
    for (int i = 0; i < 7; i++)
      asm volatile("ld.global.nc.v4.u32 {%0,%1,%2,%3}, [%4];" : "=r"(kr[4 * i]), "=r"(kr[4 * i + 1]), "=r"(kr[4 * i + 2]), "=r"(kr[4 * i + 3]) : "l"(P.dft + 512 * i + 4 * t));
    K.fe = 0x3d803d80u;
  }
  asm volatile("barrier.cluster.arrive.relaxed.aligned;" ::: "memory");
  uint32_t fo = sm + 1024 * (lm >> 1) + 256 * w + 32 * lj + (((lm ^ (lj >> 2)) & 1) << 4), smt = sm + 16 * t;
  int ownb = rank - 2 * (lm >> 1) - (w >> 1);
  const uint32_t vo = SCR + (wg == 3 ? 8192 : wg * SCR_SZ);
  uint32_t va = sm + vo + (2 * (lm & 1) + (lm >> 1)) * 1024 + w * 256 + lj * 16;
  fo = __shfl_sync(0xffffffffu, fo, lane);
  asm volatile("" : "+r"(smt), "+r"(ownb), "+r"(va));
  const uint32_t sm16 = (sm & 0x3FFFF) >> 4;
  if (wg == 3) {
    const int lt = 8 * (lj >> 1) + 2 * lm + (lj & 1);
    const uint32_t seg = 512 * rank;
    uint32_t rem = mapa(sm, g), xd = rem + SIG + seg + 128 * w + 16 * (c ^ (w & 1)), lrow = sm + (64 * w + (lt >> 3) + 4 * (lt & 7)) * PITCH;
    asm volatile("" : "+r"(rem), "+r"(xd), "+r"(lrow));
    if (w == 2) {
      const uint32_t sg = lane >= 8 ? 0x80008000u : 0u;
      if (lane < 28) sts128(sm + PAR2 + lane * 16, pv.x ^ sg, pv.y ^ sg, pv.z ^ sg, pv.w ^ sg);
    } else if (w == 3 && lane < RMAX) {
      sts32(sm + PAR + lane * PAR_SZ + 1024, __float_as_uint(rbf(expf(bf_lo(pv.x)))));
      sts32(sm + PAR + lane * PAR_SZ + 1028, pv.z << 16);
      sts32(sm + PAR3 + lane * 4, pv.y);
      if (lane == 0) { sts32(sm + PAR3 + 32, (pv.w + 1) & 31u); __stcg(P.epoch + blockIdx.x, pv.w + 1); }
    }
    TS(96 + 1);
    bar_sync(0, 512);
    if (w == 3 && elect()) {
      tma4(sm + RAWK, &mk, ch0, rank * 8 - 1, bars + 8 * B_KV);
      tma4(sm + RAWV, &mv, ch0, rank * 8, bars + 8 * B_KV);
    }
    __syncwarp();
    asm volatile("barrier.cluster.wait.aligned;" ::: "memory");
    TS(96 + 2);
    mbar_wait(bars + 8 * (B_Q + (w >> 1)));
    TSW(96 + 4 + w);
#pragma unroll 1
    for (int i = 0; i < RMAX; i++) {
      const int r = i;
      uint32_t v[2][4];
#pragma unroll
      for (int b = 0; b < 2; b++) ldsm4t(v[b], lrow + RAWQ + b * 32 * PITCH + 16 * GO(r));
#pragma unroll
      for (int b = 0; b < 2; b++) st_async4(xd + r * 4096 + 64 * b, v[b][0], v[b][1], v[b][2], v[b][3], rem + BARS + 8 * (B_U + r));
      if (i == P.gate_at) {
    uint32_t gw[RMAX];
#pragma unroll
    for (int r = 0; r < RMAX; r++) gw[r] = lds32(sm + PAR2 + 16 * r + 4 * c);
    float gs[4][4];
    const uint32_t qa = sm + RAWQ + (64 * w + (lane & 15)) * PITCH + 16 * (lane >> 4), qb = sm + RAWQ + (64 * w + lane) * PITCH + 64;
#pragma unroll
    for (int m = 0; m < 4; m++) {
      uint32_t v[4];
      gs[m][0] = gs[m][1] = gs[m][2] = gs[m][3] = 0.f;
      ldsm4(v, qa + 16 * m * PITCH); rowsum16(gs[m], v, gw[0], gw[1]);
      ldsm4(v, qa + 16 * m * PITCH + 32); rowsum16(gs[m], v, gw[2], gw[3]);
    }
#pragma unroll
    for (int m = 0; m < 2; m++) {
      uint32_t v[4];
      ldsm4(v, qb + 32 * m * PITCH); mma8(gs[2 * m], hmul(v[0], gw[4]), hmul(v[1], gw[4]), 0x3f803f80u); mma8(gs[2 * m + 1], hmul(v[2], gw[4]), hmul(v[3], gw[4]), 0x3f803f80u);
    }
    const float s0 = (c & 2) ? ((c & 1) ? gs[3][0] : gs[2][0]) : ((c & 1) ? gs[1][0] : gs[0][0]);
    const float s1 = (c & 2) ? ((c & 1) ? gs[3][2] : gs[2][2]) : ((c & 1) ? gs[1][2] : gs[0][2]);
    const uint32_t tag = lds32(sm + PAR3 + 32);
    __stcg((uint2*)P.gate_part + cl * (S_LEN / 2) + 128 * rank + t, make_uint2((__float_as_uint(s0) & ~31u) | tag, (__float_as_uint(s1) & ~31u) | tag));
      }
    }
    TSW(96 + 8 + w);
    bar_sync(NB_WG + 3, 128);
    if (w == 3 && elect()) {
      fence_async();
#pragma unroll 1
      for (int r = 0; r < RMAX; r++)
        asm volatile("cp.async.bulk.tensor.2d.shared::cluster.global.mbarrier::complete_tx::bytes [%0], [%1, {%3, %4}], [%2];"
                     ::"r"(sm + TAPA + r * 4096), "l"(&mt), "r"(bars + 8 * B_T), "r"(0), "r"((ch0 + 8 * GO(r) + rank) * 128) : "memory");
    }
    __syncwarp();
    TS(96 + 12);
    mbar_wait(bars + 8 * B_KV);
    TS(96 + 13);
    {
      const int lt2 = lt - 4;
      const uint32_t lrow2 = sm + (64 * w + ((lt2 >= 0) ? (lt2 >> 3) : 3 - 32) + 4 * (lt2 & 7)) * PITCH;
#pragma unroll 1
      for (int i = 0; i < RMAX; i++) {
          const int rr = i;
          const int go = 16 * GO(rr);
          const uint2 sw = lds64(sm + PAR2 + 128 + 4 * go + 8 * g);
          const uint32_t w0 = prmt(sw.x, 0, 0x1010), w1 = prmt(sw.x, 0, 0x3232), w2 = prmt(sw.y, 0, 0x1010), w3 = prmt(sw.y, 0, 0x3232);
          uint32_t k4[2][4], k0[2], k1[2], vv[2][4];
#pragma unroll
          for (int b = 0; b < 2; b++) {
            ldsm2t(k0[b], k1[b], lrow2 + RAWK + (b + 1) * 32 * PITCH + go);
            ldsm4t(k4[b], lrow + RAWK + (b + 1) * 32 * PITCH + go);
            ldsm4t(vv[b], lrow + RAWV + b * 32 * PITCH + go);
          }
#pragma unroll
          for (int b = 0; b < 2; b++) {
            uint32_t o[4];
            const uint32_t* v = vv[b];
            const uint32_t R[6] = {k0[b], k1[b], k4[b][0], k4[b][1], k4[b][2], k4[b][3]};
            uint32_t O[5];
#pragma unroll
            for (int i = 0; i < 5; i++) O[i] = prmt(R[i], R[i + 1], 0x5432);
#pragma unroll
            for (int i = 0; i < 4; i++) {
              o[i] = hmul(hfma(R[i + 2], w0, hfma(O[i + 1], w1, hfma(R[i + 1], w2, hmul(O[i], w3)))), v[i]);
            }
            st_async4(xd + (5 + rr) * 4096 + 64 * b, o[0], o[1], o[2], o[3], rem + BARS + 8 * (B_U + 5 + rr));
          }
        if (rr == 0 && w == 0) {
          mbar_wait(bars + 8 * B_T);
          if (lane < RMAX) { sts32(sm + TAPA + lane * 4096, hadd(lds32(sm + TAPA + lane * 4096), lds32(sm + PAR3 + 4 * lane))); mbar_arrive(bars + 8 * (B_U + 5 + lane)); }
          __syncwarp();
        }
      }
    }
    TS(96 + 14);
    {
      const uint32_t tag = lds32(sm + PAR3 + 32);
      float s0, s1;
#pragma unroll 1
      for (int n = 0, bad = 1; n < (1 << 20) && bad; n++) {
        uint2 gp[NCL];
#pragma unroll
        for (int k = 0; k < NCL; k++) asm volatile("ld.relaxed.gpu.global.v2.u32 {%0,%1}, [%2];" : "=r"(gp[k].x), "=r"(gp[k].y) : "l"(P.gate_part + k * S_LEN + 256 * rank + 2 * t) : "memory");
        bad = -2 * NCL * (int)tag; s0 = 0.f; s1 = 0.f;
#pragma unroll
        for (int k = 0; k < NCL; k++) { bad += gp[k].x + gp[k].y; s0 += __uint_as_float(gp[k].x); s1 += __uint_as_float(gp[k].y); }
        bad &= 31;
      }
      s0 = rbf(s0); s1 = rbf(s1);
      const uint32_t gg = pack_bf(__fdividef(-1.f, 1.f + __expf(-s0)), __fdividef(-1.f, 1.f + __expf(-s1)));
      const uint32_t ga = sm + GBUF + seg + 128 * w + 64 * (c >> 1) + 16 * ((g & 3) ^ (w & 1)) + 8 * (c & 1) + 2 * (g >> 2);
      sts16(ga, gg); sts16(ga + 4, gg >> 16);
    }
    fence_async();
    bar_sync(NB_WG + 3, 128);
    if (t == 0) mbar_arrive(bars + 8 * B_G);
    if (elect()) {
#pragma unroll
      for (int k = 1; k <= 2; k++) {
        const uint32_t rb = mapa(sm, (rank + 2 * w + k) & 7);
        if (k == 1 || w < 3) bulk_send(rb + seg + GBUF, sm + GBUF + seg, rb + BARS + 8 * B_G);
      }
    }
    TS(96 + 15);
    mbar_wait(bars + 8 * B_Y);
    TS(96 + 16);
  } else {
    const uint32_t scr = sm + SCR + wg * SCR_SZ;
#pragma unroll 1
    for (uint32_t ks_ = wg == 0 ? KL0 : wg == 1 ? KL1 : KL2;; ks_ >>= 4) {
      const int r = ks_ & 7;
      const bool first = (0xb >> r) & 1;
      uint32_t kd = sm16 + (SCR + wg * SCR_SZ) / 16 + (8 << 16);
      asm volatile("" : "+r"(kd));
      kd = __shfl_sync(0xffffffffu, kd, 0);
      if (first) {
    if (tid < 320) {
      const uint32_t pr = sm + PAR + (tid >> 6) * PAR_SZ;
      sts128(pr + (tid & 63) * 16, pv.x, pv.y, pv.z, pv.w);
      if (w & 1) {
        uint32_t mx = __vmaxu2(__vmaxu2(pv.x & 0x7fff7fffu, pv.y & 0x7fff7fffu), __vmaxu2(pv.z & 0x7fff7fffu, pv.w & 0x7fff7fffu));
        mx = __reduce_max_sync(0xffffffffu, max(mx & 0xffffu, mx >> 16));
        const uint32_t ex = min(max(mx >> 7, 1u), 253u);
        if (lane == 0) { sts32(pr + 1032, (254u - ex) << 23); sts32(pr + 1036, ex << 23); }
      }
    }
        TS(wg * 32 + 1);
        bar_sync(0, 512);
      }
      TS(wg * 32 + 2 + 4 * (first ? 0 : r < 3 && (wg == 0 ? KL0 : wg == 1 ? KL1 : KL2) > 0xff ? 2 : 1));
      const uint32_t cmp = scr + CMP;
      if (STAG == 2 && first && wg) bar_sync(NB_STAG + (wg != SECOND), 256);
      KSetup ks = ksetup(sm + PAR + r * PAR_SZ, t);
      if (STAG == 1 && first && wg) bar_sync(NB_STAG + (wg != SECOND), 256);
      const uint32_t so = scr + ((t >> 4) & 3) * 512 + (t & 15) * 16;
      if (first) TS(wg * 32 + 3);
      kstage(ks, so + (w >> 1) * 8192, so + 16384 + (w >> 1) * 6144);
      if (first) TS(wg * 32 + 4);
      fence_async();
      if (STAG && first && (wg != 3 - SECOND)) bar_arrive(NB_STAG + (wg == 0 ? 0 : wg == SECOND ? 1 : 2), 256);
      bar_sync(NB_WG + wg, 128);
      float d[24];
      wg_fence();
      kmma<0>(d, mkdesc(kd, 128));
      wg_commit();
      if (first) TS(wg * 32 + 5);
      const uint4 sc4 = lds128(sm + PAR + r * PAR_SZ + 1024);
      wg_wait<0>();
      if (first) TS(wg * 32 + 22);
      {
        const float sc = 2.f * __uint_as_float(sc4.x) * __uint_as_float(sc4.w);
        const int j = 16 * (w & 1) + g;
        const float skip = t == 0 ? __uint_as_float(sc4.y) : 0.f;
        const uint32_t cb = cmp + (w >> 1) * CMP_H;
        const uint32_t a1 = cb + 4 * (c < 2 ? 128 + 2 * j + c : 128 + 32 * c + j);
        if (w >= 2) {
#pragma unroll
          for (int i = 0; i < 12; i++) { d[i] = d[12 + i] * sc; asm volatile("" : "+f"(d[i])); }
        } else {
          d[0] = fmaf(d[0], sc, skip);
#pragma unroll
          for (int i = 1; i < 12; i++) { d[i] *= sc; asm volatile("" : "+f"(d[i])); }
        }
        kcompact(d, cb + 4 * (4 * j + c), a1, a1 + (c < 2 ? 64 : 32), cb + 2 * (512 + 64 * c + j), c < 2, (t & 63) == 2);
      }
      bar_sync(NB_WG + wg, 128);
      if (first) TS(wg * 32 + 23);
      const uint32_t tb = sm + KT + r * SCR_SZ + 16 * (t ^ (lm & 1));
      const uint32_t ua = cmp + 1024 + 4 * (t >> 1), ub = cmp + 1024 + 4 * ((t + 1) >> 1);
      uint32_t u0, u1;
      if (w == 0) {
        const uint4 q = lds128(cmp + 16 * lane), q2 = lds128(cmp + CMP_H + 16 * lane);
        u0 = cmp32(ua); u1 = cmp32(ub);
        sts128(tb, hadd(q.x, q2.x), hadd(q.y, q2.y), hadd(q.z, q2.z), hadd(q.w, q2.w));
      } else if (w == 1) {
        uint2 q = lds64(cmp + 512 + 8 * lane);
        const uint2 q2 = lds64(cmp + CMP_H + 512 + 8 * lane);
        const uint32_t nx = cmp32(cmp + 520 + 8 * lane);
        u1 = cmp32(ub); u0 = cmp32(ua);
        q.x = hadd(q.x, q2.x); q.y = hadd(q.y, q2.y);
        sts128(tb, prmt(q.x, 0, 0x1010), prmt(q.x, q.y, 0x5432), prmt(q.y, 0, 0x1010), prmt(q.y, nx, 0x5432));
      } else {
        const uint32_t q = cmp32(cmp + 512 + 4 * t), nx = cmp32(cmp + 516 + 4 * t);
        u0 = cmp32(ua); u1 = cmp32(ub);
        sts128(tb, prmt(q, 0, 0x1010), q, prmt(q, 0, 0x3232), prmt(nx, 0, 0x1010));
      }
      const bool odd = t & 1;
      const uint32_t aa = prmt(u0, u1, odd ? 0x3232 : 0x1010), bb = prmt(u0, u1, odd ? 0x5454 : 0x3232);
      sts128(tb + 2048, aa, aa, odd ? bb : u0, bb);
      if (first) TS(wg * 32 + 24);
      if (r < 3) break;
      mbar_arrive(bars + 8 * (B_U + r));
    }
    __syncwarp();
  }
  {
    const uint32_t ro = RECV + rank * RECV_PITCH;
#pragma unroll 1
    for (uint32_t us = wg == 0 ? TL0 : wg == 1 ? TL1 : wg == 2 ? TL2 : TL3; us; us >>= 4) {
      const int u = us & 15;
      const bool isA = u >= 5;
      const int r = isA ? u - 5 : u;
      TS(wg * 32 + 2 + 4 * it);
      mbar_wait(bars + 8 * (B_U + u));
      TS(wg * 32 + 3 + 4 * it);
      float dy[32];
      uint32_t y[8];
      const uint32_t ys = smt + KT + r * SCR_SZ;
      const uint32_t sy = fft_conv(dy, K, smt, sm16, SIG + u * 4096, isA ? TAPA + r * 4096 : KT + r * SCR_SZ, sm + MX + 4 * wid, vo, va, NB_WG + wg);
      if (!isA) {
        fft_finish(y, dy, sy);
        TS(wg * 32 + 4 + 4 * it);
        sts128(ys, y[0], y[1], y[2], y[3]);
        sts128(ys + 2048, y[4], y[5], y[6], y[7]);
        mbar_arrive(bars + 8 * (B_Y + u));
      } else {
        uint32_t q4[2][4], g4[2][4];
        uint4 b4[2];
        mbar_wait(bars + 8 * B_G);
        mbar_wait(bars + 8 * (B_Y + r));
#pragma unroll
        for (int b = 0; b < 2; b++) { ldsm4(q4[b], fo + SIG + r * 4096 + 2048 * b); ldsm4(g4[b], fo + GBUF + 2048 * b); b4[b] = lds128(ys + 2048 * b); }
        fft_finish(y, dy, sy);
        TS(wg * 32 + 4 + 4 * it);
#pragma unroll
        for (int b = 0; b < 2; b++) {
          uint32_t o[4];
          const uint32_t bb[4] = {b4[b].x, b4[b].y, b4[b].z, b4[b].w};
#pragma unroll
          for (int i = 0; i < 4; i++) o[i] = hfma(g4[b][i], hmul(q4[b][i], y[4 * b + i]), hfma(g4[b][i], bb[i], bb[i]));
          stsm4(fo + 2048 * b + (ownb == 4 * b ? ro - 512 * rank + r * RECV_SZ : SIG + r * 4096), o);
        }
        fence_async();
        __syncwarp();
        const bool mine = (w >> 1) == (rank & 1);
        if (mine && lane == 0) mbar_arrive(bars + 8 * (B_O + r));
        if (elect()) {
#pragma unroll
          for (int i = 1; i <= 4; i++) {
            const int b = (rank >> 1) ^ (i & 3);
            const uint32_t rb = mapa(sm, 2 * b + (w >> 1));
            if (i < 4 || !mine) bulk_send<256>(rb + ro + r * RECV_SZ + 256 * (w & 1), sm + SIG + r * 4096 + 1024 * b + 256 * w, rb + BARS + 8 * (B_O + r));
          }
        }
      }
      TS(wg * 32 + 5 + 4 * it);
    }
  }
  const int ow = (OUTMAP >> (4 * wg)) & 3;
  if (ow) {
    const bool one = ow == 3;
    const int r0 = one ? 0 : ow;
    if (wg < 3) asm volatile("barrier.cluster.wait.aligned;" ::: "memory");
    {
      const uint32_t ra = sm + RECV + r0 * RECV_SZ + lj * RECV_PITCH + 128 * w + ((lm ^ (w & 1)) << 4);
      const int row = 64 * w + lane;
      const uint32_t ot = sm + OUTB + 8192 * (ow - 1);
      const uint32_t oa = one ? ot + 16 * row : ot + 32 * row + (((row >> 2) & 1) << 4);
      const CUtensorMap* mo = one ? &mo8 : &mo16;
      if (elect()) asm volatile("prefetch.tensormap [%0];" ::"l"(mo) : "memory");
      uint32_t osrc = ot + (one ? 1024 : 2048) * w, oc0 = ch0 + 8 * GO(r0), oc1 = 256 * rank + 64 * w;
      asm volatile("" : "+r"(osrc), "+r"(oc0), "+r"(oc1), "+l"(mo));
      uint32_t v0[4], v1[4];
      if (!one) {
        mbar_wait(bars + 8 * (B_O + r0 + 2));
        ldsm4t(v0, ra + 2 * RECV_SZ); ldsm4t(v1, ra + 2 * RECV_SZ + 64);
        stsm4(oa ^ 16, v0); stsm4((oa ^ 16) + 1024, v1);
      }
      mbar_wait(bars + 8 * (B_O + r0));
      TS(wg * 32 + 26);
      ldsm4t(v0, ra); ldsm4t(v1, ra + 64);
      stsm4(oa, v0); stsm4(oa + (one ? 512 : 1024), v1);
      asm volatile("barrier.cluster.arrive.relaxed.aligned;" ::: "memory");
      fence_async();
      __syncwarp();
      if (elect()) tma_store(mo, osrc, oc0, oc1);
      asm volatile("cp.async.bulk.commit_group;" ::: "memory");
      asm volatile("cp.async.bulk.wait_group.read 0;" ::: "memory");
    }
    asm volatile("barrier.cluster.wait.aligned;" ::: "memory");
    TS(wg * 32 + 27);
    if (wg == 2) { TG(127); TS_DUMP(); }
  }
}

__global__ void gate_kernel(const bf16* q, const bf16* gw, unsigned int* part, const unsigned int* epoch) {
  const int slot = blockIdx.x * 8 + (threadIdx.x >> 5), lane = threadIdx.x & 31;
  const int t = (slot >> 1) & 127, w = t >> 5, g = (t & 31) >> 2, c = t & 3;
  const int row = (slot & ~255) + 64 * w + 32 * (c >> 1) + 8 * (g & 3) + 4 * (c & 1) + (g >> 2) + 2 * (slot & 1);
  float s = 0.f;
  for (int d = lane; d < D_CH; d += 32) s += rbf(__bfloat162float(q[row * D_CH + d]) * __bfloat162float(gw[d]));
  for (int o = 16; o; o >>= 1) s += __shfl_xor_sync(0xffffffffu, s, o);
  if (lane < NCL) part[lane * S_LEN + slot] = ((lane ? 0u : __float_as_uint(s)) & ~31u) | ((epoch[0] + 1) & 31u);
}

typedef CUresult (*EncodeFn)(CUtensorMap*, CUtensorMapDataType, cuuint32_t, void*, const cuuint64_t*, const cuuint64_t*, const cuuint32_t*, const cuuint32_t*,
                             CUtensorMapInterleave, CUtensorMapSwizzle, CUtensorMapL2promotion, CUtensorMapFloatOOBfill);

static void make_map(EncodeFn fn, CUtensorMap* m, void* p, int hi) {
  cuuint64_t dims[4] = {(cuuint64_t)D_CH, 4, 8, S_LEN / 32};
  cuuint64_t strides[3] = {8ull * D_CH * 2, (cuuint64_t)D_CH * 2, 32ull * D_CH * 2};
  cuuint32_t box[4] = {RMAX * 8, 4, 8, (cuuint32_t)hi};
  cuuint32_t es[4] = {1, 1, 1, 1};
  fn(m, CU_TENSOR_MAP_DATA_TYPE_BFLOAT16, 4, p, dims, strides, box, es, CU_TENSOR_MAP_INTERLEAVE_NONE, CU_TENSOR_MAP_SWIZZLE_NONE,
     CU_TENSOR_MAP_L2_PROMOTION_L2_128B, CU_TENSOR_MAP_FLOAT_OOB_FILL_NONE);
}

static void make_out_map(EncodeFn fn, CUtensorMap* m, void* p, int nch) {
  cuuint64_t dims[2] = {(cuuint64_t)D_CH, (cuuint64_t)S_LEN};
  cuuint64_t strides[1] = {(cuuint64_t)D_CH * 2};
  cuuint32_t box[2] = {(cuuint32_t)nch, 64};
  cuuint32_t es[2] = {1, 1};
  fn(m, CU_TENSOR_MAP_DATA_TYPE_BFLOAT16, 2, p, dims, strides, box, es, CU_TENSOR_MAP_INTERLEAVE_NONE,
     nch == 16 ? CU_TENSOR_MAP_SWIZZLE_32B : CU_TENSOR_MAP_SWIZZLE_NONE, CU_TENSOR_MAP_L2_PROMOTION_NONE, CU_TENSOR_MAP_FLOAT_OOB_FILL_NONE);
}

extern "C" void kernel_launch(void* const* d_in, const int* in_sizes, int n_in, void* d_out, int out_size) {
  static EncodeFn fn = nullptr;
  static int coresident = 0;
  static void *gp = nullptr, *ep = nullptr, *dp = nullptr;
  if (!fn) {
    void* p = nullptr;
    cudaDriverEntryPointQueryResult qr;
    cudaGetDriverEntryPoint("cuTensorMapEncodeTiled", &p, cudaEnableDefault, &qr);
    fn = (EncodeFn)p;
    cudaGetSymbolAddress(&gp, g_gate_part);
    cudaGetSymbolAddress(&ep, g_epoch);
    cudaGetSymbolAddress(&dp, g_dft);
    cudaFuncSetAttribute(fused_kernel, cudaFuncAttributeMaxDynamicSharedMemorySize, SMEM_TOTAL);
    cudaLaunchConfig_t cfg = {};
    cfg.gridDim = dim3(NCL * CLS); cfg.blockDim = dim3(512); cfg.dynamicSmemBytes = SMEM_TOTAL;
    cudaLaunchAttribute at[1];
    at[0].id = cudaLaunchAttributeClusterDimension; at[0].val.clusterDim.x = CLS; at[0].val.clusterDim.y = 1; at[0].val.clusterDim.z = 1;
    cfg.attrs = at; cfg.numAttrs = 1;
    int n = 0;
    coresident = cudaOccupancyMaxActiveClusters(&n, fused_kernel, &cfg) == cudaSuccess && n >= NCL;
    (void)cudaGetLastError();
  }
  CUtensorMap mq, mk, mv, mt, mo8, mo16;
  make_out_map(fn, &mo8, d_out, 8);
  make_out_map(fn, &mo16, d_out, 16);
  {
    cuuint64_t dims[2] = {16, (cuuint64_t)D_CH * 128};
    cuuint64_t strides[1] = {32};
    cuuint32_t box[2] = {16, 128};
    cuuint32_t es[2] = {1, 1};
    fn(&mt, CU_TENSOR_MAP_DATA_TYPE_BFLOAT16, 2, d_in[4], dims, strides, box, es, CU_TENSOR_MAP_INTERLEAVE_NONE, CU_TENSOR_MAP_SWIZZLE_32B,
       CU_TENSOR_MAP_L2_PROMOTION_L2_128B, CU_TENSOR_MAP_FLOAT_OOB_FILL_NONE);
  }
  make_map(fn, &mq, d_in[0], 4);
  make_map(fn, &mk, d_in[1], 9);
  make_map(fn, &mv, d_in[2], 8);
  Params P;
  P.shift_k = (const bf16*)d_in[3]; P.ssm_D = (const bf16*)d_in[5];
  for (int i = 0; i < 4; i++) P.s4[i] = (const bf16*)d_in[7 + i];
  P.ldt = (const bf16*)d_in[11]; P.dskip = (const bf16*)d_in[12]; P.gate_w = (const bf16*)d_in[13];
  P.dft = (const uint32_t*)dp;
  P.gate_part = (unsigned int*)gp; P.epoch = (unsigned int*)ep;
  P.gate_at = coresident ? 1 : -1;
  if (!coresident) gate_kernel<<<S_LEN / 8, 256, 0, cudaStreamPerThread>>>((const bf16*)d_in[0], P.gate_w, P.gate_part, P.epoch);
  fused_kernel<<<NCL * CLS, 512, SMEM_TOTAL, cudaStreamPerThread>>>(mq, mk, mv, mt, mo8, mo16, P);
}
```
